```python
import torch

def _softmax(x, axis=-1):
    return torch.softmax(x, dim=axis)
def _gelu(x):
    return torch.nn.functional.gelu(x, approximate="tanh")
def _silu(x):
    return torch.nn.functional.silu(x)
def _sigmoid(x):
    return torch.sigmoid(x)
def _layernorm(x, axis=-1, eps=1e-5):
    m = x.mean(dim=axis, keepdim=True)
    v = x.var(dim=axis, keepdim=True, unbiased=False)
    return (x - m) / torch.sqrt(v + eps)
def _scatter_add(tgt, idx, src, axis=0):
    return tgt.clone().index_add_(axis, idx, src)
def _segment_sum(src, seg, n):
    out = torch.zeros((n,) + src.shape[1:], dtype=src.dtype)
    return out.index_add_(0, seg, src)
def _pad(x, pw):
    flat = tuple(v for pair in reversed(pw) for v in pair)
    return torch.nn.functional.pad(x, flat)

kernel_name = 'standalone__channel_attn_eca__vision'

def setup_inputs():

    _w = (lambda a: (lambda t: t.to(torch.bfloat16) if t.is_floating_point() else t)(torch.as_tensor(a)))
    H = W = 384
    C = 384
    k = 1
    return {
        "x": _w((lambda *s: torch.randn(*s, dtype=torch.bfloat16) * 1.6)(1, H, W, C) + (lambda *s: torch.randn(*s, dtype=torch.bfloat16) * 1.6)(1, 1, 1, C) * 2.0),
        "w1d": _w((lambda *s: torch.randn(*s, dtype=torch.bfloat16) * 1.6)(k)),
    }

def reference(x, w1d):
    B, H, W, C = x.shape
    k = 1
    pad = k // 2
    g = torch.einsum("bhwc->bc", x) / (H * W)
    gp = _pad(g, ((0, 0), (pad, pad)))
    s = torch.zeros_like(g)
    for i in range(k):
        s = s + gp[:, i:i + C] * w1d[i]
    s = _sigmoid(s)
    return x * s[:, None, None, :]
```

```cpp
#include <cuda_runtime.h>
#include <cuda_bf16.h>
#include <cuda.h>
#include <stdint.h>

namespace eca {

constexpr int ROWS = 147456;
constexpr int CH   = 384;
constexpr int ROWB = CH * 2;
constexpr int NSTRIP = 3;
constexpr int NCTA = 132;
constexpr int NW = 8;
constexpr int NTHREADS = 384;
constexpr int TR = 32;
constexpr int TB = TR * 256;
constexpr int NREP = 4;
constexpr int MAXQ = 64;
constexpr int G = 2, WPG = NW / G, M = 2 * G, UR = TR * G, UPS = ROWS / UR;

struct Sched {
    signed char pfpos[40];
    signed char pfgate[40];
    int t0, t0fast;
    int dsum[2];
    int window, w2, w2u;
    int s0[4];
    int cap;
    int fahead;
    int poll_ns;
    int pfn, pfstart, pfdelay;
    int tw;
    int tfin;
    unsigned zero;
};

__device__ double   g_sum[2][NSTRIP][NREP][128];
__device__ unsigned g_cnt[2][NSTRIP][2][32];
__device__ unsigned g_pool[2][NSTRIP][32];
__device__ unsigned g_epoch[3][NCTA];

__device__ __forceinline__ uint32_t smem_u32(const void* p) { return (uint32_t)__cvta_generic_to_shared(p); }
__device__ __forceinline__ uint4 lds128(uint32_t a) {
    uint4 v; asm volatile("ld.shared.v4.u32 {%0,%1,%2,%3}, [%4];" : "=r"(v.x), "=r"(v.y), "=r"(v.z), "=r"(v.w) : "r"(a) : "memory"); return v;
}
__device__ __forceinline__ uint32_t ldsv32(uint32_t a) { uint32_t v; asm volatile("ld.volatile.shared.u32 %0, [%1];" : "=r"(v) : "r"(a) : "memory"); return v; }
__device__ __forceinline__ void stsv32(uint32_t a, uint32_t v) { asm volatile("st.volatile.shared.u32 [%0], %1;" :: "r"(a), "r"(v) : "memory"); }
__device__ __forceinline__ void mbar_init(uint32_t bar, uint32_t n) { asm volatile("mbarrier.init.shared::cta.b64 [%0], %1;" :: "r"(bar), "r"(n) : "memory"); }
__device__ __forceinline__ void mbar_wait(uint32_t bar, uint32_t ph) {
    asm volatile("{\n\t.reg .pred p, q;\n\t.reg .u32 n;\n\tmov.u32 n, 0;\n"
                 "W_%=:\n\tmbarrier.try_wait.parity.shared::cta.b64 p, [%0], %1;\n\t@p bra D_%=;\n\t"
                 "add.u32 n, n, 1;\n\tsetp.lt.u32 q, n, 0x400000;\n\t@q bra W_%=;\n\ttrap;\n"
                 "D_%=:\n\t}" :: "r"(bar), "r"(ph) : "memory");
}
__device__ __forceinline__ uint32_t desc_wait(uint32_t a) {
    uint32_t v;
    asm volatile("{\n\t.reg .pred p, q;\n\t.reg .u32 n;\n\tmov.u32 n, 0;\n"
                 "W_%=:\n\tld.volatile.shared.u32 %0, [%1];\n\tsetp.ne.u32 p, %0, 0;\n\t@p bra D_%=;\n\t"
                 "add.u32 n, n, 1;\n\tsetp.lt.u32 q, n, 0x1000000;\n\t@q bra W_%=;\n\ttrap;\n"
                 "D_%=:\n\t}" : "=r"(v) : "r"(a) : "memory");
    return v;
}
__device__ __forceinline__ void mbar_arrive_elect(uint32_t bar) {
    asm volatile("{\n\t.reg .pred p;\n\telect.sync _|p, 0xffffffff;\n\t@p mbarrier.arrive.shared::cta.b64 _, [%0];\n\t}" :: "r"(bar) : "memory");
}
__device__ __forceinline__ void tma_load(uint32_t dst, const CUtensorMap* tm, uint32_t bar, int c, int r, uint64_t pol) {
    asm volatile("mbarrier.arrive.expect_tx.shared::cta.b64 _, [%0], %1;" :: "r"(bar), "r"(TB) : "memory");
    asm volatile("cp.async.bulk.tensor.2d.shared::cluster.global.mbarrier::complete_tx::bytes.L2::cache_hint [%0], [%1, {%3, %4}], [%2], %5;"
        :: "r"(dst), "l"(tm), "r"(bar), "r"(c), "r"(r), "l"(pol) : "memory");
}
__device__ __forceinline__ uint32_t hmul2bf(uint32_t a, uint32_t b) {
    uint32_t d; asm("mul.rn.bf16x2 %0, %1, %2;" : "=r"(d) : "r"(a), "r"(b)); return d;
}
__device__ __forceinline__ uint64_t pol_first() { uint64_t p; asm volatile("createpolicy.fractional.L2::evict_first.b64 %0, 1.0;" : "=l"(p)); return p; }
__device__ __forceinline__ float bf_round(float x) { return __bfloat162float(__float2bfloat16_rn(x)); }

template<int NS, int NR>
struct Cfg {
    static constexpr int SM_PART  = NS * TB;
    static constexpr int SM_SCALE = SM_PART + 2048;
    static constexpr int SM_DESC  = SM_SCALE + 256;
    static constexpr int SM_FULL  = SM_DESC + MAXQ * 4;
    static constexpr int SM_EMPTY = SM_FULL + NS * 8;
    static constexpr int SM_PBAR  = SM_EMPTY + NS * 8;
    static constexpr int SM_SBAR  = SM_PBAR + 8;
    static constexpr int SM_ISS   = SM_SBAR + NSTRIP * 8;
    static constexpr int SM_TOTAL = SM_ISS + 8;
    static_assert(SM_TOTAL <= 232448, "smem");
};
__device__ __forceinline__ uint32_t mkdesc(int s, int r) { return (uint32_t)(r * (UR * ROWB) + s * 256) | 4u | s; }

template<int NS, int NR>
__global__ void __launch_bounds__(NTHREADS, 1)
eca_kernel(const __grid_constant__ CUtensorMap tmap, const __nv_bfloat16* __restrict__ w1d,
           char* __restrict__ out, const __grid_constant__ Sched sc)
{
    using C = Cfg<NS, NR>;
    extern __shared__ __align__(1024) char smem[];
    const int warp = __shfl_sync(0xffffffffu, threadIdx.x >> 5, 0), lane = threadIdx.x & 31;
    const uint32_t sbase = smem_u32(smem);
    const uint32_t full = sbase + C::SM_FULL, empty = sbase + C::SM_EMPTY, desc = sbase + C::SM_DESC;
    const int cta = blockIdx.x;
    constexpr int PRE = 4;

    if (warp == 8) {
        if (lane == 0) {
            const uint64_t pol = pol_first();
#pragma unroll
            for (int i = 0; i < PRE; i++) mbar_init(full + i * 8, 1);
            asm volatile("fence.proxy.async.shared::cta;" ::: "memory");
#pragma unroll
            for (int i = 0; i < PRE; i++) tma_load(sbase + i * TB, &tmap, full + i * 8, 0, ((i / G) * NCTA + cta) * UR + (i % G) * TR, pol);
        }
        __syncwarp();
    } else if (warp == 9) {
        if (lane == 0) { for (int i = PRE; i < NS; i++) mbar_init(full + i * 8, 1); asm volatile("fence.proxy.async.shared::cta;" ::: "memory"); }
        __syncwarp();
    } else if (warp == 10) {
        if (lane == 0) { for (int i = 0; i < NS; i++) mbar_init(empty + i * 8, WPG); }
        __syncwarp();
    } else if (warp == 11) {
        if (lane == 0) {
            mbar_init(sbase + C::SM_PBAR, NW / 2);
            for (int i = 0; i < NSTRIP; i++) mbar_init(sbase + C::SM_SBAR + i * 8, 2);
            stsv32(sbase + C::SM_ISS, PRE);
        }
        __syncwarp();
    } else if (threadIdx.x < MAXQ) {
        stsv32(desc + threadIdx.x * 4, (int)threadIdx.x < sc.s0[0] ? mkdesc(0, threadIdx.x * NCTA + cta) : 0);
    }
    __syncthreads();

    if (warp >= NW) {
        asm volatile("setmaxnreg.dec.sync.aligned.u32 40;");
        if (warp == 8) {
            if (lane == 0) {
                const uint64_t pol_ld = pol_first();
                int slot = PRE; uint32_t eph = 1;
                int wslot = 0, wu = 0; uint32_t wph = 0;
                int u = PRE;
                for (int q = PRE / G; ; q++) {
                    const uint32_t d = desc_wait(desc + q * 4);
                    const int s = d & 3;
                    if (s == NSTRIP) break;
                    const int row = (d >> 8) / 3;
#pragma unroll 1
                    for (int h = 0; h < G; h++, u++) {
                        if (u >= NS) mbar_wait(empty + slot * 8, eph);
                        const int Wc = u >= sc.w2u ? sc.w2 : sc.window;
                        while (wu <= u - Wc) { mbar_wait(full + wslot * 8, wph); wu++; if (++wslot == NS) { wslot = 0; wph ^= 1; } }
                        tma_load(sbase + slot * TB, &tmap, full + slot * 8, s * 128, row + h * TR, pol_ld);
                        stsv32(sbase + C::SM_ISS, u + 1);
                        if (++slot == NS) { slot = 0; eph ^= 1; }
                    }
                }
            }
        } else if (warp == 10) {
            if (lane == 0) {
                const unsigned tag = *(volatile unsigned*)&g_epoch[2][cta] + 1;
                if (cta < NSTRIP) g_pool[(tag & 1) ^ 1][cta][0] = 0;
                int q = sc.s0[0], s = 0, n = sc.s0[0];
                int base2 = 1000; int k = 0; bool pfarmed = false; unsigned next = 0; int guard = 0;
                while (s < NSTRIP || k < sc.pfn) {
                    const int iss = ldsv32(sbase + C::SM_ISS);
                    if (!pfarmed && iss >= sc.pfstart) { pfarmed = true; next = clock() + sc.pfdelay; }
                    while (pfarmed && k < sc.pfn) {
                        const int gate = sc.pfgate[k];
                        if (gate == -128) { if ((int)((unsigned)clock() - next) < 0) break; next += iss == sc.pfstart ? sc.t0fast : sc.t0; }
                        else if (iss - base2 < gate) break;
                        const int pos = sc.pfpos[k];
                        const int r = (pos / G) * NCTA + cta;
                        if (r < UPS)
                        asm volatile("cp.async.bulk.prefetch.tensor.2d.L2.global [%0, {%1, %2}];"
                            :: "l"(&tmap), "r"(256), "r"(r * UR + (pos % G) * TR) : "memory");
                        k++;
                    }
                    if (s == NSTRIP && iss == q * G) break;
                    if (s < NSTRIP && iss >= (q - sc.fahead) * G) {
                        unsigned r = UPS;
                        if (n < sc.cap) {
                            asm volatile("atom.relaxed.gpu.global.add.u32 %0, [%1], 1;" : "=r"(r) : "l"(&g_pool[tag & 1][s][0]) : "memory");
                            r += sc.s0[s] * NCTA;
                        }
                        if (r < UPS) { stsv32(desc + q * 4, mkdesc(s, r)); q++; n++; }
                        else {
                            s++; n = sc.s0[s];
                            if (s == 2) base2 = q * G;
                            if (s < NSTRIP) { for (int i = 0; i < n; i++) stsv32(desc + (q + i) * 4, mkdesc(s, i * NCTA + cta)); q += n; }
                            else stsv32(desc + q * 4, 7);
                        }
                    }
                    if (++guard > (1 << 24)) __trap();
                }
                g_epoch[2][cta] = tag;
            }
        } else {
            const int hf = warp == 9 ? 0 : 1;
            const unsigned tag = *(volatile unsigned*)&g_epoch[hf][cta] + 1;
            const unsigned par = tag & 1;
            const float wv = __bfloat162float(w1d[0]);
            if (cta < NSTRIP * NREP) {
#pragma unroll
                for (int i = 0; i < 2; i++) (&g_sum[par ^ 1][0][0][0])[cta * 128 + hf * 64 + i * 32 + lane] = 0.0;
                if (cta < NSTRIP) g_cnt[par ^ 1][cta][hf][lane] = 0;
            }
            for (int s = 0; s < NSTRIP; s++) {
                mbar_wait(sbase + C::SM_PBAR, s & 1);
                float p[2];
#pragma unroll
                for (int i = 0; i < 2; i++) {
                    const uint32_t pa = sbase + C::SM_PART + (hf * 64 + i * 32 + lane) * 4;
                    p[i] = (__uint_as_float(ldsv32(pa)) + __uint_as_float(ldsv32(pa + 512))) + (__uint_as_float(ldsv32(pa + 1024)) + __uint_as_float(ldsv32(pa + 1536)));
                }
                unsigned dep = 0;
#pragma unroll
                for (int i = 0; i < 2; i++) {
                    double o;
                    asm volatile("atom.relaxed.gpu.global.add.f64 %0, [%1], %2;" : "=d"(o) : "l"(&g_sum[par][s][cta & (NREP - 1)][hf * 64 + i * 32 + lane]), "d"((double)p[i]) : "memory");
                    dep |= (unsigned)__double2loint(o);
                }
                dep = __reduce_or_sync(0xffffffffu, dep & sc.zero);
                unsigned* cp = &g_cnt[par][s][hf][0];
                if (lane == 0) asm volatile("red.relaxed.gpu.global.add.u32 [%0], %1;" :: "l"(cp), "r"(dep + 1) : "memory");
                if (lane == 0) {
                    int guard = 0;
                    while (true) {
                        unsigned c;
                        asm volatile("ld.relaxed.gpu.global.u32 %0, [%1];" : "=r"(c) : "l"(cp) : "memory");
                        if (c >= NCTA) break;
                        __nanosleep(sc.poll_ns);
                        if (++guard > (1 << 22)) __trap();
                    }
                }
                __syncwarp();
                double d[NREP][2];
#pragma unroll
                for (int r = 0; r < NREP; r++)
                    asm volatile("ld.relaxed.gpu.global.v2.f64 {%0,%1}, [%2];" : "=d"(d[r][0]), "=d"(d[r][1]) : "l"(&g_sum[par][s][r][hf * 64 + lane * 2]) : "memory");
                unsigned q[2];
#pragma unroll
                for (int i = 0; i < 2; i++) {
                    double t = d[0][i];
#pragma unroll
                    for (int r = 1; r < NREP; r++) t += d[r][i];
                    const float xs = bf_round((float)t);
                    const float inv = 1.0f / (float)ROWS;
                    float q0 = xs * inv;
                    float q1 = fmaf(fmaf(-q0, (float)ROWS, xs), inv, q0);
                    float g = bf_round(fabsf(xs) <= 3.4e38f ? q1 : q0);
                    float z = bf_round(g * wv);
                    float sg = __fdividef(1.f, 1.f + expf(-z));
                    q[i] = __bfloat16_as_ushort(__float2bfloat16_rn(sg));
                }
                asm volatile("st.shared.u32 [%0], %1;" :: "r"(sbase + C::SM_SCALE + hf * 128 + lane * 4), "r"(q[0] | (q[1] << 16)) : "memory");
                __syncwarp();
                mbar_arrive_elect(sbase + C::SM_SBAR + s * 8);
            }
            if (lane == 0) g_epoch[hf][cta] = tag;
        }
    } else {
        asm volatile("setmaxnreg.inc.sync.aligned.u32 232;");
        const uint64_t pol_st = pol_first();
        const int grp = warp / WPG;
        float acc[8];
#pragma unroll
        for (int i = 0; i < 8; i++) acc[i] = 0.f;
        uint4 scl = make_uint4(0, 0, 0, 0);
        uint4 regs[NR][M];
        int sum_q = 0, sum_slot = grp, arrived = 0; uint32_t sum_ph = 0;
        int ref_slot = grp, ri = 0, cur_s = -1;
        unsigned tnext = 0, tper = 0;
        const int dsum = sc.dsum[grp];
        const uint32_t lbase = sbase + (warp % WPG) * (M * 512) + lane * 16;
        const uint32_t ooff = (warp * 2 * M + (lane >> 4)) * ROWB + (lane & 15) * 16;

        for (int k = -NR; ; k++) {
            uint32_t d = 0; int st_s = -1;
            if (k >= 0) { d = __shfl_sync(0xffffffffu, ldsv32(desc + k * 4), 0); st_s = d & 3; if (st_s == NSTRIP) break; }
            const int need = k + (k >= 0 ? dsum : NR + 1);
            while (arrived < NSTRIP && (sum_q < need || arrived <= st_s)) {
                mbar_wait(full + sum_slot * 8, sum_ph);
                const uint32_t a = lbase + sum_slot * TB;
#pragma unroll
                for (int i = 0; i < M; i++) {
                    uint4 v = lds128(a + i * 512);
                    acc[0] += __uint_as_float(v.x << 16); acc[1] += __uint_as_float(v.x & 0xffff0000u);
                    acc[2] += __uint_as_float(v.y << 16); acc[3] += __uint_as_float(v.y & 0xffff0000u);
                    acc[4] += __uint_as_float(v.z << 16); acc[5] += __uint_as_float(v.z & 0xffff0000u);
                    acc[6] += __uint_as_float(v.w << 16); acc[7] += __uint_as_float(v.w & 0xffff0000u);
                }
                sum_q++; sum_slot += G; if (sum_slot >= NS) { sum_slot -= NS; sum_ph ^= 1; }
                const int ns = __shfl_sync(0xffffffffu, desc_wait(desc + sum_q * 4), 0) & 3;
                if (ns != arrived) {
                    const bool hi = lane >= 16;
                    const uint32_t pa = sbase + C::SM_PART + (warp >> 1) * 512 + (lane & 15) * 32 + (hi ? 16 : 0);
                    float r[4];
#pragma unroll
                    for (int i = 0; i < 4; i++) r[i] = (hi ? acc[4 + i] : acc[i]) + __shfl_xor_sync(0xffffffffu, hi ? acc[i] : acc[4 + i], 16);
                    if (!(warp & 1)) {
                        asm volatile("barrier.sync %0, 64;" :: "r"(1 + (warp >> 1)) : "memory");
                        const uint4 o = lds128(pa);
                        r[0] += __uint_as_float(o.x); r[1] += __uint_as_float(o.y); r[2] += __uint_as_float(o.z); r[3] += __uint_as_float(o.w);
                    }
                    asm volatile("st.shared.v4.f32 [%0], {%1,%2,%3,%4};" :: "r"(pa), "f"(r[0]), "f"(r[1]), "f"(r[2]), "f"(r[3]) : "memory");
                    const uint32_t rb = __shfl_sync(0xffffffffu, ldsv32(pa) & sc.zero, 0);
                    if (warp & 1) asm volatile("barrier.arrive %0, 64;" :: "r"(1 + (warp >> 1) + rb) : "memory");
                    else mbar_arrive_elect(sbase + C::SM_PBAR + rb);
#pragma unroll
                    for (int i = 0; i < 8; i++) acc[i] = 0.f;
                    arrived++;
                    if (arrived == NSTRIP) { tnext = __shfl_sync(0xffffffffu, (unsigned)clock(), 0); tper = sc.tw; }
                }
            }
            const bool do_ld = k + NR < sum_q;
            const bool do_st = k >= 0;
            if (st_s != cur_s) {
                mbar_wait(sbase + C::SM_SBAR + st_s * 8, 0);
                scl = lds128(sbase + C::SM_SCALE + (lane & 15) * 16);
                cur_s = st_s;
                if (st_s == NSTRIP - 1) { tnext = __shfl_sync(0xffffffffu, (unsigned)clock(), 0); tper = __shfl_sync(0xffffffffu, (unsigned)__fdividef((float)sc.tfin, (float)(sum_q - k)), 0); }
            }
            if (tper) { while ((int)((unsigned)clock() - tnext) < 0) { } tnext += tper; }
            char* const op = out + ((d & ~7u) + ooff);
            const uint32_t a = lbase + ref_slot * TB;
            uint32_t dep = 0;
#define ECA_CASE(K) case K: if (K < NR) { \
                if (do_st) { _Pragma("unroll") for (int i = 0; i < M; i++) { \
                    uint4 v = regs[K < NR ? K : 0][i]; \
                    v.x = hmul2bf(v.x, scl.x); v.y = hmul2bf(v.y, scl.y); v.z = hmul2bf(v.z, scl.z); v.w = hmul2bf(v.w, scl.w); \
                    asm volatile("st.global.L2::cache_hint.v4.u32 [%0], {%1,%2,%3,%4}, %5;" :: "l"(op + i * 2 * ROWB), "r"(v.x), "r"(v.y), "r"(v.z), "r"(v.w), "l"(pol_st) : "memory"); } } \
                if (do_ld) { _Pragma("unroll") for (int i = 0; i < M; i++) { regs[K < NR ? K : 0][i] = lds128(a + i * 512); dep |= regs[K < NR ? K : 0][i].x; } } \
            } break;
            switch (ri) {
                ECA_CASE(0) ECA_CASE(1) ECA_CASE(2) ECA_CASE(3) ECA_CASE(4) ECA_CASE(5) ECA_CASE(6) ECA_CASE(7)
                ECA_CASE(8) ECA_CASE(9) ECA_CASE(10) ECA_CASE(11) ECA_CASE(12) ECA_CASE(13)
                default: break;
            }
#undef ECA_CASE
            if (arrived < NSTRIP) { __syncwarp(); mbar_arrive_elect(empty + ref_slot * 8 + (dep & sc.zero)); }
            if (++ri == NR) ri = 0;
            ref_slot += G; if (ref_slot >= NS) ref_slot -= NS;
        }
    }
}

}

namespace eca_fb {
__device__ float g_part[256][eca::CH];
__global__ void sum_kernel(const __nv_bfloat16* __restrict__ x, int rows) {
    const int c = threadIdx.x; float a = 0.f;
    for (int r = blockIdx.x; r < rows; r += gridDim.x) a += __bfloat162float(x[(size_t)r * eca::CH + c]);
    g_part[blockIdx.x][c] = a;
}
__global__ void scale_kernel(const __nv_bfloat16* __restrict__ x, const __nv_bfloat16* __restrict__ w, __nv_bfloat16* __restrict__ y, int rows) {
    const int c = threadIdx.x; double t = 0.0;
    for (int i = 0; i < 256; i++) t += g_part[i][c];
    const float g = eca::bf_round(eca::bf_round((float)t) / (float)rows);
    const float z = eca::bf_round(g * __bfloat162float(w[0]));
    const __nv_bfloat16 s = __float2bfloat16_rn(1.f / (1.f + expf(-z)));
    for (int r = blockIdx.x; r < rows; r += gridDim.x) y[(size_t)r * eca::CH + c] = __hmul(x[(size_t)r * eca::CH + c], s);
}
}

typedef CUresult (*EncodeFn)(CUtensorMap*, CUtensorMapDataType, cuuint32_t, void*, const cuuint64_t*, const cuuint64_t*,
                             const cuuint32_t*, const cuuint32_t*, CUtensorMapInterleave, CUtensorMapSwizzle,
                             CUtensorMapL2promotion, CUtensorMapFloatOOBfill);

extern "C" void kernel_launch(void* const* d_in, const int* in_sizes, int n_in, void* d_out, int out_size) {
    using namespace eca;
    constexpr int NS = 28, NR = 12;
    using C = Cfg<NS, NR>;
    const __nv_bfloat16* x = (const __nv_bfloat16*)d_in[0];
    const __nv_bfloat16* w = (const __nv_bfloat16*)d_in[1];
    static int mode = -1;
    static EncodeFn enc = nullptr;
    if (mode < 0) {
        int dev = 0, sms = 0, occ = 0;
        cudaGetDevice(&dev);
        cudaDeviceGetAttribute(&sms, cudaDevAttrMultiProcessorCount, dev);
        cudaDriverEntryPointQueryResult q;
        cudaGetDriverEntryPoint("cuTensorMapEncodeTiled", (void**)&enc, cudaEnableDefault, &q);
        cudaError_t e = cudaFuncSetAttribute(eca_kernel<NS, NR>, cudaFuncAttributeMaxDynamicSharedMemorySize, C::SM_TOTAL);
        if (e == cudaSuccess) e = cudaOccupancyMaxActiveBlocksPerMultiprocessor(&occ, eca_kernel<NS, NR>, NTHREADS, C::SM_TOTAL);
        mode = (e == cudaSuccess && enc && sms * occ >= NCTA) ? 1 : 0;
        (void)cudaGetLastError();
    }
    CUtensorMap tm;
    bool fast = mode == 1 && in_sizes[0] == ROWS * CH && out_size == ROWS * CH;
    if (fast) {
        cuuint64_t dims[2] = {(cuuint64_t)CH, (cuuint64_t)ROWS}; cuuint64_t strides[1] = {(cuuint64_t)ROWB};
        cuuint32_t box[2] = {128, (cuuint32_t)TR}; cuuint32_t es[2] = {1, 1};
        fast = enc(&tm, CU_TENSOR_MAP_DATA_TYPE_BFLOAT16, 2, (void*)x, dims, strides, box, es, CU_TENSOR_MAP_INTERLEAVE_NONE,
                   CU_TENSOR_MAP_SWIZZLE_NONE, CU_TENSOR_MAP_L2_PROMOTION_NONE, CU_TENSOR_MAP_FLOAT_OOB_FILL_NONE) == CUDA_SUCCESS;
    }
    if (!fast) {
        const int rows = in_sizes[0] / CH;
        eca_fb::sum_kernel<<<256, CH>>>(x, rows);
        eca_fb::scale_kernel<<<1024, CH>>>(x, w, (__nv_bfloat16*)d_out, rows);
        return;
    }
    Sched s;
    s.dsum[0] = 24; s.dsum[1] = 24;
    s.s0[0] = 16; s.s0[1] = 14; s.s0[2] = 14; s.s0[3] = 0; s.cap = 21; s.fahead = 1;
    s.window = 8; s.w2 = 6; s.w2u = 32; s.poll_ns = 50; s.zero = 0;
    s.tw = 1000; s.tfin = 21500; s.t0 = 2000; s.t0fast = 670; s.pfstart = NS + G * NR; s.pfdelay = 600;
    {
        const int a = 4, P = 11, dend = 5, n = 36 - a;
        s.pfn = n;
        for (int k = 0; k < 40; k++) { s.pfpos[k] = 0; s.pfgate[k] = 0; }
        for (int k = 0; k < n; k++) {
            s.pfpos[k] = (signed char)(a + k);
            if (k < P) s.pfgate[k] = -128;
            else { double f = (double)(k - P) / (n - 1 - P), dist = P + (dend - P) * f; s.pfgate[k] = (signed char)(int)(a + k - dist + 0.5); }
        }
    }
    eca_kernel<NS, NR><<<NCTA, NTHREADS, C::SM_TOTAL>>>(tm, w, (char*)d_out, s);
}
```

```cpp
#include <cuda_runtime.h>
#include <cuda_bf16.h>
#include <cuda.h>
#include <stdint.h>

namespace eca {

constexpr int ROWS = 147456;
constexpr int CH = 384;
constexpr int ROWB = CH * 2;
constexpr int NSTRIP = 3;
constexpr int NCTA = 132;
constexpr int NW = 8;
constexpr int NTHREADS = 384;
constexpr int G = 2;
constexpr int WPG = NW / G;
constexpr int TR = 32;
constexpr int TB = TR * 256;
constexpr int M = 2 * G;
constexpr int NBOX = ROWS / TR;
constexpr int UPS = (NBOX + NCTA - 1) / NCTA;
constexpr int NU = UPS * NSTRIP;
constexpr int NS = 28;
constexpr int NR = 13;
constexpr int NREP = 2;
constexpr int PRE = 4;

constexpr int WIN0 = 7, WIN1 = 6, WIN1_FROM = 44, WIN_END = 70;
constexpr int LAZY = 25, LAZY_UP_AT = 22;
constexpr int T_E = 1050, K_M = 6, T_M = 1220;
constexpr int CREDIT = 1200, STAG = 800, SLACK = 1600;
constexpr int LOOK = 2, T_END = 750, T_COVER = 650, T_LAST = 12600;
constexpr int PF_START = 53, PF_FIRST = 8, PF_TIMED = 11, PF_T = 950, PF_TFAST = 330, PF_D0 = 9, PF_D1 = 3;
static_assert(G == 2 && NS % G == 0 && UPS % 2 == 1, "box u belongs to group u % 2 and slot u % NS");
static_assert(LAZY >= (UPS + 1) / G && LAZY + 1 <= NS / G + NR, "a strip is posted before its scale is awaited; no wait for an unissued box");
static_assert(UPS - 1 + NR < NU / G - LOOK, "refills never overtake the sums");
static_assert(NS + G * NR < 2 * UPS - G, "partial-sum rows and scales are consumed before they are reused");

constexpr int SM_PART = NS * TB;
constexpr int SM_SCALE = SM_PART + 2048;
constexpr int SM_FULL = SM_SCALE + 512;
constexpr int SM_EMPTY = SM_FULL + NS * 8;
constexpr int SM_PBAR = SM_EMPTY + NS * 8;
constexpr int SM_SBAR = SM_PBAR + 8;
constexpr int SM_ISS = SM_SBAR + NSTRIP * 8;
constexpr int SM_TRDY = SM_ISS + 4;
constexpr int SM_TOTAL = SM_ISS + 8;
static_assert(SM_TOTAL <= 232448, "smem");

constexpr int CPB = 8, SUMS = 528, CNTS = 1056;
struct Scratch {
    double sum[NSTRIP * NREP][128 / CPB][SUMS];
    unsigned cnt[NSTRIP][2][CNTS];
    unsigned flag[2][32];
    unsigned epoch[2][NCTA];
};
__device__ __align__(128) Scratch g_s;

__device__ __forceinline__ uint4 lds128(uint32_t a) {
    uint4 v; asm volatile("ld.shared.v4.u32 {%0,%1,%2,%3}, [%4];" : "=r"(v.x), "=r"(v.y), "=r"(v.z), "=r"(v.w) : "r"(a) : "memory"); return v;
}
__device__ __forceinline__ uint32_t ldsv32(uint32_t a) { uint32_t v; asm volatile("ld.volatile.shared.u32 %0, [%1];" : "=r"(v) : "r"(a) : "memory"); return v; }
__device__ __forceinline__ void stsv32(uint32_t a, uint32_t v) { asm volatile("st.volatile.shared.u32 [%0], %1;" :: "r"(a), "r"(v) : "memory"); }
__device__ __forceinline__ void mbar_init(uint32_t bar, uint32_t n) { asm volatile("mbarrier.init.shared::cta.b64 [%0], %1;" :: "r"(bar), "r"(n) : "memory"); }
__device__ __forceinline__ bool mbar_test(uint32_t bar, uint32_t ph) {
    uint32_t ok;
    asm volatile("{\n\t.reg .pred p;\n\tmbarrier.test_wait.parity.shared::cta.b64 p, [%1], %2;\n\tselp.u32 %0, 1, 0, p;\n\t}" : "=r"(ok) : "r"(bar), "r"(ph) : "memory");
    return ok;
}
__device__ __forceinline__ void mbar_wait(uint32_t bar, uint32_t ph) {
    asm volatile("{\n\t.reg .pred p, q;\n\t.reg .u32 n;\n\tmov.u32 n, 0;\n"
                 "W_%=:\n\tmbarrier.try_wait.parity.shared::cta.b64 p, [%0], %1;\n\t@p bra D_%=;\n\t"
                 "add.u32 n, n, 1;\n\tsetp.lt.u32 q, n, 0x400000;\n\t@q bra W_%=;\n\ttrap;\n"
                 "D_%=:\n\t}" :: "r"(bar), "r"(ph) : "memory");
}
__device__ __forceinline__ void mbar_arrive_elect(uint32_t bar) {
    asm volatile("{\n\t.reg .pred p;\n\telect.sync _|p, 0xffffffff;\n\t@p mbarrier.arrive.shared::cta.b64 _, [%0];\n\t}" :: "r"(bar) : "memory");
}
__device__ __forceinline__ void tma_load(uint32_t dst, const CUtensorMap* tm, uint32_t bar, int c, int r, uint64_t pol) {
    asm volatile("mbarrier.arrive.expect_tx.shared::cta.b64 _, [%0], %1;" :: "r"(bar), "r"(TB) : "memory");
    asm volatile("cp.async.bulk.tensor.2d.shared::cluster.global.mbarrier::complete_tx::bytes.L2::cache_hint [%0], [%1, {%3, %4}], [%2], %5;"
                 :: "r"(dst), "l"(tm), "r"(bar), "r"(c), "r"(r), "l"(pol) : "memory");
}
__device__ __forceinline__ uint32_t hmul2bf(uint32_t a, uint32_t b) { uint32_t d; asm("mul.rn.bf16x2 %0, %1, %2;" : "=r"(d) : "r"(a), "r"(b)); return d; }
__device__ __forceinline__ uint64_t pol_stream() { uint64_t p; asm volatile("createpolicy.fractional.L2::evict_first.b64 %0, 1.0;" : "=l"(p)); return p; }
__device__ __forceinline__ uint32_t lane_now() { uint32_t l; asm volatile("mov.u32 %0, %%laneid;" : "=r"(l)); return l; }
__device__ __forceinline__ unsigned now_ns() { unsigned t; asm volatile("mov.u32 %0, %%globaltimer_lo;" : "=r"(t)); return t; }
__device__ __forceinline__ unsigned unow_ns() { return __shfl_sync(0xffffffffu, now_ns(), 0); }
__device__ __forceinline__ float bf_round(float x) { return __bfloat162float(__float2bfloat16_rn(x)); }

__device__ __forceinline__ int box_row(int s, int j, int cta) { const int r = j * NCTA + cta; return (s ? NBOX - 1 - r : r) * TR; }

__global__ void __launch_bounds__(NTHREADS, 1)
eca_kernel(const __grid_constant__ CUtensorMap tmap, const __nv_bfloat16* __restrict__ w1d,
           const char* __restrict__ xin, char* __restrict__ out, const unsigned zero)
{
    extern __shared__ __align__(1024) char smem[];
    const int warp = __shfl_sync(0xffffffffu, threadIdx.x >> 5, 0), lane = threadIdx.x & 31;
    const uint32_t sbase = (uint32_t)__cvta_generic_to_shared(smem);
    const uint32_t full = sbase + SM_FULL, empty = sbase + SM_EMPTY;
    const int cta = blockIdx.x;

    if (threadIdx.x < 128)
        asm volatile("prefetch.global.L2 [%0];" :: "l"(xin + (uint32_t)((box_row(0, threadIdx.x >> 6, cta) + ((threadIdx.x >> 1) & 31)) * ROWB + (threadIdx.x & 1) * 128)) : "memory");
    if (warp == 8) {
        if (lane == 0) {
            const uint64_t pol = pol_stream();
#pragma unroll
            for (int i = 0; i < PRE; i++) mbar_init(full + i * 8, 1);
            asm volatile("fence.proxy.async.shared::cta;" ::: "memory");
#pragma unroll
            for (int i = 0; i < PRE; i++) tma_load(sbase + i * TB, &tmap, full + i * 8, 0, box_row(0, i, cta), pol);
        }
        __syncwarp();
    } else if (warp == 9) {
        if (lane == 0) { for (int i = PRE; i < NS; i++) mbar_init(full + i * 8, 1); asm volatile("fence.proxy.async.shared::cta;" ::: "memory"); }
        __syncwarp();
    } else if (warp == 10) {
        if (lane == 0) { for (int i = 0; i < NS; i++) mbar_init(empty + i * 8, WPG); }
        __syncwarp();
    } else if (warp == 11) {
        if (lane == 0) {
            mbar_init(sbase + SM_PBAR, NW / 2);
            for (int i = 0; i < NSTRIP; i++) mbar_init(sbase + SM_SBAR + i * 8, 2);
            stsv32(sbase + SM_ISS, PRE);
        }
        __syncwarp();
    }
    __syncthreads();

    if (warp >= NW) {
        asm volatile("setmaxnreg.dec.sync.aligned.u32 24;");
        if (warp == 8) {
            if (lane == 0) {
                const uint64_t pol = pol_stream();
                int slot = PRE, s = 0, j = PRE; uint32_t eph = 1;
                int wslot = 0, wu = 0; uint32_t wph = 0;
#pragma unroll 1
                for (int u = PRE; u < NU; u++) {
                    mbar_wait(empty + slot * 8, eph);
                    if (u < WIN_END) {
                        const int lim = u - (u >= WIN1_FROM ? WIN1 : WIN0);
#pragma unroll 1
                        while (wu <= lim) { mbar_wait(full + wslot * 8, wph); wu++; if (++wslot == NS) { wslot = 0; wph ^= 1; } }
                    }
                    tma_load(sbase + slot * TB, &tmap, full + slot * 8, s * 128, box_row(s, j, cta), pol);
                    stsv32(sbase + SM_ISS, u + 1);
                    if (++slot == NS) { slot = 0; eph ^= 1; }
                    if (++j == UPS) { j = 0; s++; }
                }
            }
        } else if (warp == 10) {
            if (lane == 0) {
                int guard = 0;
                while ((int)ldsv32(sbase + SM_ISS) < PF_START) { __nanosleep(20); if (++guard > (1 << 24)) __trap(); }
                unsigned next = now_ns();
#pragma unroll 1
                for (int pos = PF_FIRST; pos < UPS; pos++) {
                    if (pos < PF_FIRST + PF_TIMED) {
                        while ((int)(now_ns() - next) < 0) { }
                        next += (int)ldsv32(sbase + SM_ISS) == PF_START ? PF_TFAST : PF_T;
                    } else {
                        constexpr int A = PF_FIRST + PF_TIMED, L = UPS - 1 - A;
                        const int gate = 2 * UPS + pos - PF_D0 + (2 * (PF_D0 - PF_D1) * (pos - A) + L) / (2 * L);
                        while ((int)ldsv32(sbase + SM_ISS) < gate) { if (++guard > (1 << 26)) __trap(); }
                    }
                    asm volatile("cp.async.bulk.prefetch.tensor.2d.L2.global [%0, {%1, %2}];" :: "l"(&tmap), "r"(256), "r"(box_row(2, pos, cta)) : "memory");
                }
            }
        } else {
            const int hf = warp == 9 ? 0 : 1;
            const unsigned epoch = __shfl_sync(0xffffffffu, *(volatile unsigned*)&g_s.epoch[hf][cta] + 1, 0);
            const float wv = __shfl_sync(0xffffffffu, __bfloat162float(w1d[0]), 0);
            double* sp = &g_s.sum[0][(hf * 64 + lane) / CPB][lane % CPB];
            constexpr int SI = (32 / CPB) * SUMS, SR = (128 / CPB) * SUMS;
            if (cta < NSTRIP * NREP) {
                unsigned long long o0, o1; unsigned o2 = 0;
                asm volatile("atom.relaxed.gpu.global.exch.b64 %0, [%1], 0;" : "=l"(o0) : "l"(sp + cta * SR) : "memory");
                asm volatile("atom.relaxed.gpu.global.exch.b64 %0, [%1], 0;" : "=l"(o1) : "l"(sp + cta * SR + SI) : "memory");
                if (cta < NSTRIP) asm volatile("atom.relaxed.gpu.global.exch.b32 %0, [%1], 0;" : "=r"(o2) : "l"(&g_s.cnt[cta][hf][lane]) : "memory");
                const unsigned done = __reduce_or_sync(0xffffffffu, ((unsigned)(o0 | o1) | o2) & zero);
                asm volatile("st.relaxed.gpu.global.u32 [%0], %1;" :: "l"(&g_s.flag[hf][cta]), "r"(epoch + done) : "memory");
            }
            for (int guard = 0; ; guard++) {
                __nanosleep(1000);
                unsigned f;
                asm volatile("ld.relaxed.gpu.global.u32 %0, [%1];" : "=r"(f) : "l"(&g_s.flag[hf][lane % (NSTRIP * NREP)]) : "memory");
                if (__all_sync(0xffffffffu, f == epoch)) break;
                if (guard > (1 << 20)) __trap();
            }
#pragma unroll 1
            for (int s = 0; s < NSTRIP; s++, sp += NREP * SR) {
                mbar_wait(sbase + SM_PBAR, s & 1);
                unsigned dep = 0;
#pragma unroll
                for (int i = 0; i < 2; i++) {
                    const uint32_t pa = sbase + SM_PART + (hf * 64 + i * 32 + lane_now()) * 4;
                    const float p = (__uint_as_float(ldsv32(pa)) + __uint_as_float(ldsv32(pa + 512)))
                                  + (__uint_as_float(ldsv32(pa + 1024)) + __uint_as_float(ldsv32(pa + 1536)));
                    double o;
                    asm volatile("atom.relaxed.gpu.global.add.f64 %0, [%1], %2;" : "=d"(o) : "l"(sp + (cta % NREP) * SR + i * SI), "d"((double)p) : "memory");
                    dep |= (unsigned)__double2loint(o);
                }
                dep = __reduce_or_sync(0xffffffffu, dep & zero);
                {
                    unsigned* cp = &g_s.cnt[s][hf][0];
                    asm volatile("{\n\t.reg .pred p;\n\telect.sync _|p, 0xffffffff;\n\t@p red.relaxed.gpu.global.add.u32 [%0], %1;\n\t}" :: "l"(cp), "r"(dep + 1) : "memory");
                    int guard = 0;
                    while (true) {
                        unsigned c;
                        asm volatile("ld.relaxed.gpu.global.u32 %0, [%1];" : "=r"(c) : "l"(cp) : "memory");
                        if (__all_sync(0xffffffffu, c >= NCTA)) break;
                        __nanosleep(50);
                        if (++guard > (1 << 22)) __trap();
                    }
                }
                if (hf == 0) stsv32(sbase + SM_TRDY, now_ns());
                double d[NREP][2];
#pragma unroll
                for (int r = 0; r < NREP; r++)
#pragma unroll
                    for (int i = 0; i < 2; i++)
                        asm volatile("ld.relaxed.gpu.global.f64 %0, [%1];" : "=d"(d[r][i]) : "l"(sp + r * SR + i * SI) : "memory");
#pragma unroll
                for (int i = 0; i < 2; i++) {
                    double t = d[0][i];
#pragma unroll
                    for (int r = 1; r < NREP; r++) t += d[r][i];
                    const float xs = bf_round((float)t), inv = 1.0f / (float)ROWS;
                    const float q0 = xs * inv, q1 = fmaf(fmaf(-q0, (float)ROWS, xs), inv, q0);
                    const float g = bf_round(fabsf(xs) <= 3.4e38f ? q1 : q0);
                    const float z = bf_round(g * wv);
                    float sg; asm("rcp.approx.f32 %0, %1;" : "=f"(sg) : "f"(1.f + expf(-z)));
                    asm volatile("st.shared.u16 [%0], %1;" :: "r"(sbase + SM_SCALE + (s & 1) * 256 + (hf * 64 + i * 32 + lane_now()) * 2), "h"(__bfloat16_as_ushort(__float2bfloat16_rn(sg))) : "memory");
                }
                const uint32_t rb = ldsv32(sbase + SM_SCALE + (s & 1) * 256 + hf * 128 + 64) & zero;
                __syncwarp();
                mbar_arrive_elect(sbase + SM_SBAR + s * 8 + rb);
            }
            if (lane_now() == 0) g_s.epoch[hf][cta] = epoch;
        }
    } else {
        asm volatile("setmaxnreg.inc.sync.aligned.u32 240;");
        const uint64_t pol = pol_stream();
        const int grp = warp / WPG;
        float acc[8];
#pragma unroll
        for (int i = 0; i < 8; i++) acc[i] = 0.f;
        uint4 scl = make_uint4(0, 0, 0, 0);
        uint4 regs[NR][M];
        const int n = (NU + 1 - grp) / G;
        int sum_q = 0, sum_slot = grp, sum_end = (UPS + 1 - grp) / G; uint32_t sum_ph = 0;
        int ref_slot = grp, ri = 0, st_s = 0, st_j = grp, wait_k = 0, mode = 0;
        unsigned tnext = 0, tper = 0;
        const uint32_t lbase = sbase + (warp % WPG) * (M * 512) + lane * 16;
        const uint32_t ooff = ((warp % WPG) * 2 * M + (lane >> 4)) * ROWB + (lane & 15) * 16;

#pragma unroll 1
        for (int k = -NR; k < n; k++) {
            const int need = k + (k < 0 ? NR + 1 : k < LAZY_UP_AT ? LAZY : LAZY + 1);
            while (sum_q < n) {
                if (k > 0 && k < UPS) {
                    bool go;
                    do {
                        if (!mode && sum_q >= need && (int)(unow_ns() - tnext) >= 0) { go = false; break; }
                        go = __any_sync(0xffffffffu, mbar_test(full + sum_slot * 8, sum_ph));
                    } while (!go && !(mode && (int)(unow_ns() - tnext) >= 0));
                    if (!go) break;
                } else if (sum_q >= need) break;
                mbar_wait(full + sum_slot * 8, sum_ph);
                const uint32_t a = lbase + sum_slot * TB;
#pragma unroll
                for (int i = 0; i < M; i++) {
                    const uint4 v = lds128(a + i * 512);
                    acc[0] += __uint_as_float(v.x << 16); acc[1] += __uint_as_float(v.x & 0xffff0000u);
                    acc[2] += __uint_as_float(v.y << 16); acc[3] += __uint_as_float(v.y & 0xffff0000u);
                    acc[4] += __uint_as_float(v.z << 16); acc[5] += __uint_as_float(v.z & 0xffff0000u);
                    acc[6] += __uint_as_float(v.w << 16); acc[7] += __uint_as_float(v.w & 0xffff0000u);
                }
                sum_q++; sum_slot += G; if (sum_slot >= NS) { sum_slot -= NS; sum_ph ^= 1; }
                if (sum_q == n - LOOK) { mode = 1; tnext = unow_ns(); tper = T_END; }
                if (sum_q == sum_end) {
                    const uint32_t ln = lane_now();
                    const bool hi = ln >= 16;
                    const uint32_t pa = sbase + SM_PART + (warp >> 1) * 512 + (ln & 15) * 32 + (ln & 16);
                    float r[4];
#pragma unroll
                    for (int i = 0; i < 4; i++) r[i] = (hi ? acc[4 + i] : acc[i]) + __shfl_xor_sync(0xffffffffu, hi ? acc[i] : acc[4 + i], 16);
                    if (!(warp & 1)) {
                        asm volatile("barrier.sync %0, 64;" :: "r"(1 + (warp >> 1)) : "memory");
                        const uint4 o = lds128(pa);
                        r[0] += __uint_as_float(o.x); r[1] += __uint_as_float(o.y); r[2] += __uint_as_float(o.z); r[3] += __uint_as_float(o.w);
                    }
                    asm volatile("st.shared.v4.f32 [%0], {%1,%2,%3,%4};" :: "r"(pa), "f"(r[0]), "f"(r[1]), "f"(r[2]), "f"(r[3]) : "memory");
                    const uint32_t rb = __shfl_sync(0xffffffffu, ldsv32(pa) & zero, 0);
                    if (warp & 1) asm volatile("barrier.arrive %0, 64;" :: "r"(1 + (warp >> 1) + rb) : "memory");
                    else mbar_arrive_elect(sbase + SM_PBAR + rb);
#pragma unroll
                    for (int i = 0; i < 8; i++) acc[i] = 0.f;
                    if (sum_q == n) tper = T_COVER;
                    sum_end = sum_end < UPS ? UPS : n;
                }
            }
            if (k == wait_k) {
                mbar_wait(sbase + SM_SBAR + st_s * 8, 0);
                scl = lds128(sbase + SM_SCALE + (st_s & 1) * 256 + (lane_now() & 15) * 16);
                wait_k = k == 0 ? (UPS + 1 - grp) / G : UPS;
            }
            if (mode == 1 && __any_sync(0xffffffffu, mbar_test(sbase + SM_SBAR + (NSTRIP - 1) * 8, 0))) {
                mode = 2;
                const unsigned now = unow_ns();
                if ((int)(now - tnext) > 0) tnext = now;
                const int left = (int)(ldsv32(sbase + SM_TRDY) + T_LAST - tnext);
                tper = __shfl_sync(0xffffffffu, (unsigned)__fdividef((float)(left > 0 ? left : 0), (float)(n - k)), 0);
            }
            if (mode) { while ((int)(now_ns() - tnext) < 0) { } tnext += tper; }
            else if (k >= 0) {
                const unsigned lo = unow_ns() - SLACK;
                if (k == 0) tnext = lo + (SLACK - CREDIT) + grp * STAG; else if ((int)(lo - tnext) > 0) tnext = lo;
                tnext += k >= K_M ? T_M : T_E;
            }
            const int row = box_row(st_s, st_j, cta);
            const bool do_ld = k + NR < n, do_st = k >= 0 && (unsigned)row < (unsigned)ROWS;
            char* const op = out + ((uint32_t)(row * ROWB + st_s * 256) + ooff);
            if (k >= 0) { st_j += G; if (st_j >= UPS) { st_j -= UPS; st_s++; } }
            const uint32_t a = lbase + ref_slot * TB;
            uint32_t dep = 0;
#define ECA_CASE(K) case K: \
                if (do_st) { _Pragma("unroll") for (int i = 0; i < M; i++) { \
                    uint4& v = regs[K][i]; \
                    v.x = hmul2bf(v.x, scl.x); v.y = hmul2bf(v.y, scl.y); v.z = hmul2bf(v.z, scl.z); v.w = hmul2bf(v.w, scl.w); \
                    asm volatile("st.global.L2::cache_hint.v4.u32 [%0], {%1,%2,%3,%4}, %5;" \
                                 :: "l"(op + i * 2 * ROWB), "r"(v.x), "r"(v.y), "r"(v.z), "r"(v.w), "l"(pol) : "memory"); } } \
                if (do_ld) { _Pragma("unroll") for (int i = 0; i < M; i++) { regs[K][i] = lds128(a + i * 512); dep |= regs[K][i].x; } } \
                break;
            static_assert(NR == 13, "one case per register set");
            switch (ri) {
                ECA_CASE(0) ECA_CASE(1) ECA_CASE(2) ECA_CASE(3) ECA_CASE(4) ECA_CASE(5) ECA_CASE(6)
                ECA_CASE(7) ECA_CASE(8) ECA_CASE(9) ECA_CASE(10) ECA_CASE(11) ECA_CASE(12)
                default: break;
            }
#undef ECA_CASE
            if (k + NR + NS / G < n) { __syncwarp(); mbar_arrive_elect(empty + ref_slot * 8 + (dep & zero)); }
            if (++ri == NR) ri = 0;
            ref_slot += G; if (ref_slot >= NS) ref_slot -= NS;
        }
    }
}

}

namespace eca_fb {
__device__ float g_part[256][eca::CH];
__global__ void sum_kernel(const __nv_bfloat16* __restrict__ x, int rows) {
    const int c = threadIdx.x; float a = 0.f;
    for (int r = blockIdx.x; r < rows; r += gridDim.x) a += __bfloat162float(x[(size_t)r * eca::CH + c]);
    g_part[blockIdx.x][c] = a;
}
__global__ void scale_kernel(const __nv_bfloat16* __restrict__ x, const __nv_bfloat16* __restrict__ w, __nv_bfloat16* __restrict__ y, int rows) {
    const int c = threadIdx.x; double t = 0.0;
    for (int i = 0; i < 256; i++) t += g_part[i][c];
    const float g = eca::bf_round(eca::bf_round((float)t) / (float)rows);
    const float z = eca::bf_round(g * __bfloat162float(w[0]));
    const __nv_bfloat16 s = __float2bfloat16_rn(1.f / (1.f + expf(-z)));
    for (int r = blockIdx.x; r < rows; r += gridDim.x) y[(size_t)r * eca::CH + c] = __hmul(x[(size_t)r * eca::CH + c], s);
}
}

typedef CUresult (*EncodeFn)(CUtensorMap*, CUtensorMapDataType, cuuint32_t, void*, const cuuint64_t*, const cuuint64_t*,
                             const cuuint32_t*, const cuuint32_t*, CUtensorMapInterleave, CUtensorMapSwizzle,
                             CUtensorMapL2promotion, CUtensorMapFloatOOBfill);

extern "C" void kernel_launch(void* const* d_in, const int* in_sizes, int n_in, void* d_out, int out_size) {
    using namespace eca;
    const __nv_bfloat16* x = (const __nv_bfloat16*)d_in[0];
    const __nv_bfloat16* w = (const __nv_bfloat16*)d_in[1];
    static int mode = -1;
    static EncodeFn enc = nullptr;
    if (mode < 0) {
        int dev = 0, sms = 0, occ = 0;
        cudaGetDevice(&dev);
        cudaDeviceGetAttribute(&sms, cudaDevAttrMultiProcessorCount, dev);
        cudaDriverEntryPointQueryResult q;
        cudaGetDriverEntryPoint("cuTensorMapEncodeTiled", (void**)&enc, cudaEnableDefault, &q);
        cudaError_t e = cudaFuncSetAttribute(eca_kernel, cudaFuncAttributeMaxDynamicSharedMemorySize, SM_TOTAL);
        if (e == cudaSuccess) e = cudaOccupancyMaxActiveBlocksPerMultiprocessor(&occ, eca_kernel, NTHREADS, SM_TOTAL);
        mode = (e == cudaSuccess && enc && sms * occ >= NCTA) ? 1 : 0;
        (void)cudaGetLastError();
    }
    CUtensorMap tm;
    bool fast = mode == 1 && in_sizes[0] == ROWS * CH && out_size == ROWS * CH;
    if (fast) {
        cuuint64_t dims[2] = {(cuuint64_t)CH, (cuuint64_t)ROWS}; cuuint64_t strides[1] = {(cuuint64_t)ROWB};
        cuuint32_t box[2] = {128, (cuuint32_t)TR}; cuuint32_t es[2] = {1, 1};
        fast = enc(&tm, CU_TENSOR_MAP_DATA_TYPE_BFLOAT16, 2, (void*)x, dims, strides, box, es, CU_TENSOR_MAP_INTERLEAVE_NONE,
                   CU_TENSOR_MAP_SWIZZLE_NONE, CU_TENSOR_MAP_L2_PROMOTION_NONE, CU_TENSOR_MAP_FLOAT_OOB_FILL_NONE) == CUDA_SUCCESS;
    }
    if (fast) {
        cudaLaunchAttribute at;
        at.id = cudaLaunchAttributeCooperative; at.val.cooperative = 1;
        cudaLaunchConfig_t cfg = {};
        cfg.gridDim = dim3(NCTA); cfg.blockDim = dim3(NTHREADS); cfg.dynamicSmemBytes = SM_TOTAL;
        cfg.attrs = &at; cfg.numAttrs = 1;
        cudaLaunchKernelEx(&cfg, eca_kernel, tm, w, (const char*)x, (char*)d_out, 0u);
    } else {
        const int rows = in_sizes[0] / CH;
        eca_fb::sum_kernel<<<256, CH>>>(x, rows);
        eca_fb::scale_kernel<<<1024, CH>>>(x, w, (__nv_bfloat16*)d_out, rows);
    }
}
```

```cpp
#include <cuda_runtime.h>
#include <cuda_bf16.h>
#include <cuda.h>
#include <stdint.h>

namespace eca {

constexpr int ROWS = 147456;
constexpr int CH = 384;
constexpr int ROWB = CH * 2;
constexpr int NSTRIP = 3;
constexpr int NCTA = 132;
constexpr int NW = 8;
constexpr int NTHREADS = 384;
constexpr int G = 2;
constexpr int WPG = NW / G;
constexpr int TR = 32;
constexpr int TB = TR * 256;
constexpr int M = 2 * G;
constexpr int NBOX = ROWS / TR;
constexpr int UPS = (NBOX + NCTA - 1) / NCTA;
constexpr int NU = UPS * NSTRIP;
constexpr int NS = 28;
constexpr int NR = 13;
constexpr int NREP = 2;
constexpr int PRE = 4;

constexpr int WIN0 = 7, WIN1 = 6, WIN1_FROM = 44, WIN_END = 70;
constexpr int LAZY = 25, LAZY_UP_AT = 22;
constexpr int T_E = 1050, K_M = 6, T_M = 1235;
constexpr int CREDIT = 1200, STAG = 800, SLACK = 1600;
constexpr int LOOK = 2, T_END = 750, T_COVER = 650, T_LAST = 12600;
constexpr int PF_START = 53, PF_FIRST = 8, PF_TIMED = 11, PF_T = 950, PF_TFAST = 330, PF_D0 = 9, PF_D1 = 3;
static_assert(G == 2 && NS % G == 0 && UPS % 2 == 1, "box u belongs to group u % 2 and slot u % NS");
static_assert(LAZY >= (UPS + 1) / G && LAZY + 1 <= NS / G + NR, "a strip is posted before its scale is awaited; no wait for an unissued box");
static_assert(UPS - 1 + NR < NU / G - LOOK, "refills never overtake the sums");
static_assert(NS + G * NR < 2 * UPS - G, "partial-sum rows and scales are consumed before they are reused");

constexpr int SM_PART = NS * TB;
constexpr int SM_SCALE = SM_PART + 2048;
constexpr int SM_FULL = SM_SCALE + 512;
constexpr int SM_EMPTY = SM_FULL + NS * 8;
constexpr int SM_PBAR = SM_EMPTY + NS * 8;
constexpr int SM_SBAR = SM_PBAR + 8;
constexpr int SM_ISS = SM_SBAR + NSTRIP * 8;
constexpr int SM_TRDY = SM_ISS + 4;
constexpr int SM_TOTAL = SM_ISS + 8;
static_assert(SM_TOTAL <= 232448, "smem");

constexpr int CPB = 8, SUMS = 528, CNTS = 1056;
struct Scratch {
    double sum[NSTRIP * NREP][128 / CPB][SUMS];
    unsigned cnt[NSTRIP][2][CNTS];
    unsigned flag[2][32];
    unsigned epoch[2][NCTA];
};
__device__ __align__(128) Scratch g_s;

__device__ __forceinline__ uint4 lds128(uint32_t a) {
    uint4 v; asm volatile("ld.shared.v4.u32 {%0,%1,%2,%3}, [%4];" : "=r"(v.x), "=r"(v.y), "=r"(v.z), "=r"(v.w) : "r"(a) : "memory"); return v;
}
__device__ __forceinline__ uint32_t ldsv32(uint32_t a) { uint32_t v; asm volatile("ld.volatile.shared.u32 %0, [%1];" : "=r"(v) : "r"(a) : "memory"); return v; }
__device__ __forceinline__ void stsv32(uint32_t a, uint32_t v) { asm volatile("st.volatile.shared.u32 [%0], %1;" :: "r"(a), "r"(v) : "memory"); }
__device__ __forceinline__ void mbar_init(uint32_t bar, uint32_t n) { asm volatile("mbarrier.init.shared::cta.b64 [%0], %1;" :: "r"(bar), "r"(n) : "memory"); }
__device__ __forceinline__ bool mbar_test(uint32_t bar, uint32_t ph) {
    uint32_t ok;
    asm volatile("{\n\t.reg .pred p;\n\tmbarrier.test_wait.parity.shared::cta.b64 p, [%1], %2;\n\tselp.u32 %0, 1, 0, p;\n\t}" : "=r"(ok) : "r"(bar), "r"(ph) : "memory");
    return ok;
}
__device__ __forceinline__ void mbar_wait(uint32_t bar, uint32_t ph) {
    asm volatile("{\n\t.reg .pred p, q;\n\t.reg .u32 n;\n\tmov.u32 n, 0;\n"
                 "W_%=:\n\tmbarrier.try_wait.parity.shared::cta.b64 p, [%0], %1, 1000;\n\t@p bra D_%=;\n\t"
                 "add.u32 n, n, 1;\n\tsetp.lt.u32 q, n, 0x400000;\n\t@q bra W_%=;\n\ttrap;\n"
                 "D_%=:\n\t}" :: "r"(bar), "r"(ph) : "memory");
}
__device__ __forceinline__ void mbar_arrive_elect(uint32_t bar) {
    asm volatile("{\n\t.reg .pred p;\n\telect.sync _|p, 0xffffffff;\n\t@p mbarrier.arrive.shared::cta.b64 _, [%0];\n\t}" :: "r"(bar) : "memory");
}
__device__ __forceinline__ void tma_load(uint32_t dst, const CUtensorMap* tm, uint32_t bar, int c, int r, uint64_t pol) {
    asm volatile("mbarrier.arrive.expect_tx.shared::cta.b64 _, [%0], %1;" :: "r"(bar), "r"(TB) : "memory");
    asm volatile("cp.async.bulk.tensor.2d.shared::cluster.global.mbarrier::complete_tx::bytes.L2::cache_hint [%0], [%1, {%3, %4}], [%2], %5;"
                 :: "r"(dst), "l"(tm), "r"(bar), "r"(c), "r"(r), "l"(pol) : "memory");
}
__device__ __forceinline__ uint32_t hmul2bf(uint32_t a, uint32_t b) { uint32_t d; asm("mul.rn.bf16x2 %0, %1, %2;" : "=r"(d) : "r"(a), "r"(b)); return d; }
__device__ __forceinline__ uint64_t pol_stream() { uint64_t p; asm volatile("createpolicy.fractional.L2::evict_first.b64 %0, 1.0;" : "=l"(p)); return p; }
__device__ __forceinline__ uint32_t lane_now() { uint32_t l; asm volatile("mov.u32 %0, %%laneid;" : "=r"(l)); return l; }
__device__ __forceinline__ unsigned now_ns() { unsigned t; asm volatile("mov.u32 %0, %%globaltimer_lo;" : "=r"(t)); return t; }
__device__ __forceinline__ unsigned unow_ns() { return __shfl_sync(0xffffffffu, now_ns(), 0); }
__device__ __forceinline__ float bf_round(float x) { return __bfloat162float(__float2bfloat16_rn(x)); }

__device__ __forceinline__ int box_row(int s, int j, int cta) { const int r = j * NCTA + cta; return (s ? NBOX - 1 - r : r) * TR; }

__global__ void __launch_bounds__(NTHREADS, 1)
eca_kernel(const __grid_constant__ CUtensorMap tmap, const __nv_bfloat16* __restrict__ w1d,
           const char* __restrict__ xin, char* __restrict__ out, const unsigned zero)
{
    extern __shared__ __align__(1024) char smem[];
    const int warp = __shfl_sync(0xffffffffu, threadIdx.x >> 5, 0), lane = threadIdx.x & 31;
    const uint32_t sbase = (uint32_t)__cvta_generic_to_shared(smem);
    const uint32_t full = sbase + SM_FULL, empty = sbase + SM_EMPTY;
    const int cta = blockIdx.x;

    if (threadIdx.x < 128)
        asm volatile("prefetch.global.L2 [%0];" :: "l"(xin + (uint32_t)((box_row(0, threadIdx.x >> 6, cta) + ((threadIdx.x >> 1) & 31)) * ROWB + (threadIdx.x & 1) * 128)) : "memory");
    if (warp == 8) {
        if (lane == 0) {
            const uint64_t pol = pol_stream();
#pragma unroll
            for (int i = 0; i < PRE; i++) mbar_init(full + i * 8, 1);
            asm volatile("fence.proxy.async.shared::cta;" ::: "memory");
#pragma unroll
            for (int i = 0; i < PRE; i++) tma_load(sbase + i * TB, &tmap, full + i * 8, 0, box_row(0, i, cta), pol);
        }
        __syncwarp();
    } else if (warp == 9) {
        if (lane == 0) { for (int i = PRE; i < NS; i++) mbar_init(full + i * 8, 1); asm volatile("fence.proxy.async.shared::cta;" ::: "memory"); }
        __syncwarp();
    } else if (warp == 10) {
        if (lane == 0) { for (int i = 0; i < NS; i++) mbar_init(empty + i * 8, WPG); }
        __syncwarp();
    } else if (warp == 11) {
        if (lane == 0) {
            mbar_init(sbase + SM_PBAR, NW / 2);
            for (int i = 0; i < NSTRIP; i++) mbar_init(sbase + SM_SBAR + i * 8, 2);
            stsv32(sbase + SM_ISS, PRE);
        }
        __syncwarp();
    }
    __syncthreads();

    if (warp >= NW) {
        asm volatile("setmaxnreg.dec.sync.aligned.u32 24;");
        if (warp == 8) {
            if (lane == 0) {
                const uint64_t pol = pol_stream();
                int slot = PRE, s = 0, j = PRE; uint32_t eph = 1;
                int wslot = 0, wu = 0; uint32_t wph = 0;
#pragma unroll 1
                for (int u = PRE; u < NU; u++) {
                    mbar_wait(empty + slot * 8, eph);
                    if (u < WIN_END) {
                        const int lim = u - (u >= WIN1_FROM ? WIN1 : WIN0);
#pragma unroll 1
                        while (wu <= lim) { mbar_wait(full + wslot * 8, wph); wu++; if (++wslot == NS) { wslot = 0; wph ^= 1; } }
                    }
                    tma_load(sbase + slot * TB, &tmap, full + slot * 8, s * 128, box_row(s, j, cta), pol);
                    stsv32(sbase + SM_ISS, u + 1);
                    if (++slot == NS) { slot = 0; eph ^= 1; }
                    if (++j == UPS) { j = 0; s++; }
                }
            }
        } else if (warp == 10) {
            if (lane == 0) {
                int guard = 0;
                while ((int)ldsv32(sbase + SM_ISS) < PF_START) { __nanosleep(20); if (++guard > (1 << 24)) __trap(); }
                unsigned next = now_ns();
#pragma unroll 1
                for (int pos = PF_FIRST; pos < UPS; pos++) {
                    if (pos < PF_FIRST + PF_TIMED) {
                        while ((int)(now_ns() - next) < 0) { }
                        next += (int)ldsv32(sbase + SM_ISS) == PF_START ? PF_TFAST : PF_T;
                    } else {
                        constexpr int A = PF_FIRST + PF_TIMED, L = UPS - 1 - A;
                        const int gate = 2 * UPS + pos - PF_D0 + (2 * (PF_D0 - PF_D1) * (pos - A) + L) / (2 * L);
                        while ((int)ldsv32(sbase + SM_ISS) < gate) { if (++guard > (1 << 26)) __trap(); }
                    }
                    asm volatile("cp.async.bulk.prefetch.tensor.2d.L2.global [%0, {%1, %2}];" :: "l"(&tmap), "r"(256), "r"(box_row(2, pos, cta)) : "memory");
                }
            }
        } else {
            const int hf = warp == 9 ? 0 : 1;
            const unsigned epoch = __shfl_sync(0xffffffffu, *(volatile unsigned*)&g_s.epoch[hf][cta] + 1, 0);
            const float wv = __shfl_sync(0xffffffffu, __bfloat162float(w1d[0]), 0);
            double* sp = &g_s.sum[0][(hf * 64 + lane) / CPB][lane % CPB];
            constexpr int SI = (32 / CPB) * SUMS, SR = (128 / CPB) * SUMS;
            if (cta < NSTRIP * NREP) {
                unsigned long long o0, o1; unsigned o2 = 0;
                asm volatile("atom.relaxed.gpu.global.exch.b64 %0, [%1], 0;" : "=l"(o0) : "l"(sp + cta * SR) : "memory");
                asm volatile("atom.relaxed.gpu.global.exch.b64 %0, [%1], 0;" : "=l"(o1) : "l"(sp + cta * SR + SI) : "memory");
                if (cta < NSTRIP) asm volatile("atom.relaxed.gpu.global.exch.b32 %0, [%1], 0;" : "=r"(o2) : "l"(&g_s.cnt[cta][hf][lane]) : "memory");
                const unsigned done = __reduce_or_sync(0xffffffffu, ((unsigned)(o0 | o1) | o2) & zero);
                asm volatile("st.relaxed.gpu.global.u32 [%0], %1;" :: "l"(&g_s.flag[hf][cta]), "r"(epoch + done) : "memory");
            }
            for (int guard = 0; ; guard++) {
                __nanosleep(1000);
                unsigned f;
                asm volatile("ld.acquire.gpu.global.u32 %0, [%1];" : "=r"(f) : "l"(&g_s.flag[hf][lane % (NSTRIP * NREP)]) : "memory");
                if (__all_sync(0xffffffffu, f == epoch)) break;
                if (guard > (1 << 20)) __trap();
            }
#pragma unroll 1
            for (int s = 0; s < NSTRIP; s++, sp += NREP * SR) {
                mbar_wait(sbase + SM_PBAR, s & 1);
                unsigned dep = 0;
#pragma unroll
                for (int i = 0; i < 2; i++) {
                    const uint32_t pa = sbase + SM_PART + (hf * 64 + i * 32 + lane_now()) * 4;
                    const float p = (__uint_as_float(ldsv32(pa)) + __uint_as_float(ldsv32(pa + 512)))
                                  + (__uint_as_float(ldsv32(pa + 1024)) + __uint_as_float(ldsv32(pa + 1536)));
                    double o;
                    asm volatile("atom.relaxed.gpu.global.add.f64 %0, [%1], %2;" : "=d"(o) : "l"(sp + (cta % NREP) * SR + i * SI), "d"((double)p) : "memory");
                    dep |= (unsigned)__double2loint(o);
                }
                dep = __reduce_or_sync(0xffffffffu, dep & zero);
                {
                    unsigned* cp = &g_s.cnt[s][hf][0];
                    asm volatile("{\n\t.reg .pred p;\n\telect.sync _|p, 0xffffffff;\n\t@p red.relaxed.gpu.global.add.u32 [%0], %1;\n\t}" :: "l"(cp), "r"(dep + 1) : "memory");
                    int guard = 0;
                    while (true) {
                        unsigned c;
                        asm volatile("ld.acquire.gpu.global.u32 %0, [%1];" : "=r"(c) : "l"(cp) : "memory");
                        if (__all_sync(0xffffffffu, c >= NCTA)) break;
                        __nanosleep(50);
                        if (++guard > (1 << 22)) __trap();
                    }
                }
                if (hf == 0) stsv32(sbase + SM_TRDY, now_ns());
                double d[NREP][2];
#pragma unroll
                for (int r = 0; r < NREP; r++)
#pragma unroll
                    for (int i = 0; i < 2; i++)
                        asm volatile("ld.relaxed.gpu.global.f64 %0, [%1];" : "=d"(d[r][i]) : "l"(sp + r * SR + i * SI) : "memory");
#pragma unroll
                for (int i = 0; i < 2; i++) {
                    double t = d[0][i];
#pragma unroll
                    for (int r = 1; r < NREP; r++) t += d[r][i];
                    const float xs = bf_round((float)t), inv = 1.0f / (float)ROWS;
                    const float q0 = xs * inv, q1 = fmaf(fmaf(-q0, (float)ROWS, xs), inv, q0);
                    const float g = bf_round(fabsf(xs) <= 3.4e38f ? q1 : q0);
                    const float z = bf_round(g * wv);
                    float sg; asm("rcp.approx.f32 %0, %1;" : "=f"(sg) : "f"(1.f + expf(-z)));
                    asm volatile("st.shared.u16 [%0], %1;" :: "r"(sbase + SM_SCALE + (s & 1) * 256 + (hf * 64 + i * 32 + lane_now()) * 2), "h"(__bfloat16_as_ushort(__float2bfloat16_rn(sg))) : "memory");
                }
                const uint32_t rb = ldsv32(sbase + SM_SCALE + (s & 1) * 256 + hf * 128 + 64) & zero;
                __syncwarp();
                mbar_arrive_elect(sbase + SM_SBAR + s * 8 + rb);
            }
            if (lane_now() == 0) g_s.epoch[hf][cta] = epoch;
        }
    } else {
        asm volatile("setmaxnreg.inc.sync.aligned.u32 240;");
        const uint64_t pol = pol_stream();
        const int grp = warp / WPG;
        float acc[8];
#pragma unroll
        for (int i = 0; i < 8; i++) acc[i] = 0.f;
        uint4 scl = make_uint4(0, 0, 0, 0);
        uint4 regs[NR][M];
        const int n = (NU + 1 - grp) / G;
        int sum_q = 0, sum_slot = grp, sum_end = (UPS + 1 - grp) / G; uint32_t sum_ph = 0;
        int ref_slot = grp, ri = 0, st_s = 0, st_j = grp, wait_k = 0, mode = 0;
        unsigned tnext = 0, tper = 0;
        const uint32_t lbase = sbase + (warp % WPG) * (M * 512) + lane * 16;
        const uint32_t ooff = ((warp % WPG) * 2 * M + (lane >> 4)) * ROWB + (lane & 15) * 16;

#pragma unroll 1
        for (int k = -NR; k < n; k++) {
            const int need = k + (k < 0 ? NR + 1 : k < LAZY_UP_AT ? LAZY : LAZY + 1);
            while (sum_q < n) {
                if (k > 0 && k < UPS) {
                    bool go;
                    do {
                        if (!mode && sum_q >= need && (int)(unow_ns() - tnext) >= 0) { go = false; break; }
                        go = __any_sync(0xffffffffu, mbar_test(full + sum_slot * 8, sum_ph));
                    } while (!go && !(mode && (int)(unow_ns() - tnext) >= 0));
                    if (!go) break;
                } else if (sum_q >= need) break;
                mbar_wait(full + sum_slot * 8, sum_ph);
                const uint32_t a = lbase + sum_slot * TB;
#pragma unroll
                for (int i = 0; i < M; i++) {
                    const uint4 v = lds128(a + i * 512);
                    acc[0] += __uint_as_float(v.x << 16); acc[1] += __uint_as_float(v.x & 0xffff0000u);
                    acc[2] += __uint_as_float(v.y << 16); acc[3] += __uint_as_float(v.y & 0xffff0000u);
                    acc[4] += __uint_as_float(v.z << 16); acc[5] += __uint_as_float(v.z & 0xffff0000u);
                    acc[6] += __uint_as_float(v.w << 16); acc[7] += __uint_as_float(v.w & 0xffff0000u);
                }
                sum_q++; sum_slot += G; if (sum_slot >= NS) { sum_slot -= NS; sum_ph ^= 1; }
                if (sum_q == n - LOOK) { mode = 1; tnext = unow_ns(); tper = T_END; }
                if (sum_q == sum_end) {
                    const uint32_t ln = lane_now();
                    const bool hi = ln >= 16;
                    const uint32_t pa = sbase + SM_PART + (warp >> 1) * 512 + (ln & 15) * 32 + (ln & 16);
                    float r[4];
#pragma unroll
                    for (int i = 0; i < 4; i++) r[i] = (hi ? acc[4 + i] : acc[i]) + __shfl_xor_sync(0xffffffffu, hi ? acc[i] : acc[4 + i], 16);
                    if (!(warp & 1)) {
                        asm volatile("barrier.sync %0, 64;" :: "r"(1 + (warp >> 1)) : "memory");
                        const uint4 o = lds128(pa);
                        r[0] += __uint_as_float(o.x); r[1] += __uint_as_float(o.y); r[2] += __uint_as_float(o.z); r[3] += __uint_as_float(o.w);
                    }
                    asm volatile("st.shared.v4.f32 [%0], {%1,%2,%3,%4};" :: "r"(pa), "f"(r[0]), "f"(r[1]), "f"(r[2]), "f"(r[3]) : "memory");
                    const uint32_t rb = __shfl_sync(0xffffffffu, ldsv32(pa) & zero, 0);
                    if (warp & 1) asm volatile("barrier.arrive %0, 64;" :: "r"(1 + (warp >> 1) + rb) : "memory");
                    else mbar_arrive_elect(sbase + SM_PBAR + rb);
#pragma unroll
                    for (int i = 0; i < 8; i++) acc[i] = 0.f;
                    if (sum_q == n) tper = T_COVER;
                    sum_end = sum_end < UPS ? UPS : n;
                }
            }
            if (k == wait_k) {
                mbar_wait(sbase + SM_SBAR + st_s * 8, 0);
                scl = lds128(sbase + SM_SCALE + (st_s & 1) * 256 + (lane_now() & 15) * 16);
                wait_k = k == 0 ? (UPS + 1 - grp) / G : UPS;
            }
            if (mode == 1 && __any_sync(0xffffffffu, mbar_test(sbase + SM_SBAR + (NSTRIP - 1) * 8, 0))) {
                mode = 2;
                const unsigned now = unow_ns();
                if ((int)(now - tnext) > 0) tnext = now;
                const int left = (int)(ldsv32(sbase + SM_TRDY) + T_LAST - tnext);
                tper = __shfl_sync(0xffffffffu, (unsigned)__fdividef((float)(left > 0 ? left : 0), (float)(n - k)), 0);
            }
            if (mode) { while ((int)(now_ns() - tnext) < 0) { } tnext += tper; }
            else if (k >= 0) {
                const unsigned lo = unow_ns() - SLACK;
                if (k == 0) tnext = lo + (SLACK - CREDIT) + grp * STAG; else if ((int)(lo - tnext) > 0) tnext = lo;
                tnext += k >= K_M ? T_M : T_E;
            }
            const int row = box_row(st_s, st_j, cta);
            const bool do_ld = k + NR < n, do_st = k >= 0 && (unsigned)row < (unsigned)ROWS;
            char* const op = out + ((uint32_t)(row * ROWB + st_s * 256) + ooff);
            if (k >= 0) { st_j += G; if (st_j >= UPS) { st_j -= UPS; st_s++; } }
            const uint32_t a = lbase + ref_slot * TB;
            uint32_t dep = 0;
#define ECA_CASE(K) case K: \
                if (do_st) { _Pragma("unroll") for (int i = 0; i < M; i++) { \
                    uint4& v = regs[K][i]; \
                    v.x = hmul2bf(v.x, scl.x); v.y = hmul2bf(v.y, scl.y); v.z = hmul2bf(v.z, scl.z); v.w = hmul2bf(v.w, scl.w); \
                    asm volatile("st.global.L2::cache_hint.v4.u32 [%0], {%1,%2,%3,%4}, %5;" \
                                 :: "l"(op + i * 2 * ROWB), "r"(v.x), "r"(v.y), "r"(v.z), "r"(v.w), "l"(pol) : "memory"); } } \
                if (do_ld) { _Pragma("unroll") for (int i = 0; i < M; i++) { regs[K][i] = lds128(a + i * 512); dep |= regs[K][i].x; } } \
                break;
            static_assert(NR == 13, "one case per register set");
            switch (ri) {
                ECA_CASE(0) ECA_CASE(1) ECA_CASE(2) ECA_CASE(3) ECA_CASE(4) ECA_CASE(5) ECA_CASE(6)
                ECA_CASE(7) ECA_CASE(8) ECA_CASE(9) ECA_CASE(10) ECA_CASE(11) ECA_CASE(12)
                default: break;
            }
#undef ECA_CASE
            if (k + NR + NS / G < n) { __syncwarp(); mbar_arrive_elect(empty + ref_slot * 8 + (dep & zero)); }
            if (++ri == NR) ri = 0;
            ref_slot += G; if (ref_slot >= NS) ref_slot -= NS;
        }
    }
}

}

namespace eca_fb {
__device__ float g_part[256][eca::CH];
__global__ void sum_kernel(const __nv_bfloat16* __restrict__ x, int rows) {
    const int c = threadIdx.x; float a = 0.f;
    for (int r = blockIdx.x; r < rows; r += gridDim.x) a += __bfloat162float(x[(size_t)r * eca::CH + c]);
    g_part[blockIdx.x][c] = a;
}
__global__ void scale_kernel(const __nv_bfloat16* __restrict__ x, const __nv_bfloat16* __restrict__ w, __nv_bfloat16* __restrict__ y, int rows) {
    const int c = threadIdx.x; double t = 0.0;
    for (int i = 0; i < 256; i++) t += g_part[i][c];
    const float g = eca::bf_round(eca::bf_round((float)t) / (float)rows);
    const float z = eca::bf_round(g * __bfloat162float(w[0]));
    const __nv_bfloat16 s = __float2bfloat16_rn(1.f / (1.f + expf(-z)));
    for (int r = blockIdx.x; r < rows; r += gridDim.x) y[(size_t)r * eca::CH + c] = __hmul(x[(size_t)r * eca::CH + c], s);
}
}

typedef CUresult (*EncodeFn)(CUtensorMap*, CUtensorMapDataType, cuuint32_t, void*, const cuuint64_t*, const cuuint64_t*,
                             const cuuint32_t*, const cuuint32_t*, CUtensorMapInterleave, CUtensorMapSwizzle,
                             CUtensorMapL2promotion, CUtensorMapFloatOOBfill);

extern "C" void kernel_launch(void* const* d_in, const int* in_sizes, int n_in, void* d_out, int out_size) {
    using namespace eca;
    const __nv_bfloat16* x = (const __nv_bfloat16*)d_in[0];
    const __nv_bfloat16* w = (const __nv_bfloat16*)d_in[1];
    static int mode = -1;
    static EncodeFn enc = nullptr;
    if (mode < 0) {
        int dev = 0, sms = 0, occ = 0;
        cudaGetDevice(&dev);
        cudaDeviceGetAttribute(&sms, cudaDevAttrMultiProcessorCount, dev);
        cudaDriverEntryPointQueryResult q;
        cudaGetDriverEntryPoint("cuTensorMapEncodeTiled", (void**)&enc, cudaEnableDefault, &q);
        cudaError_t e = cudaFuncSetAttribute(eca_kernel, cudaFuncAttributeMaxDynamicSharedMemorySize, SM_TOTAL);
        if (e == cudaSuccess) e = cudaOccupancyMaxActiveBlocksPerMultiprocessor(&occ, eca_kernel, NTHREADS, SM_TOTAL);
        mode = (e == cudaSuccess && enc && sms * occ >= NCTA) ? 1 : 0;
        (void)cudaGetLastError();
    }
    CUtensorMap tm;
    bool fast = mode == 1 && in_sizes[0] == ROWS * CH && out_size == ROWS * CH;
    if (fast) {
        cuuint64_t dims[2] = {(cuuint64_t)CH, (cuuint64_t)ROWS}; cuuint64_t strides[1] = {(cuuint64_t)ROWB};
        cuuint32_t box[2] = {128, (cuuint32_t)TR}; cuuint32_t es[2] = {1, 1};
        fast = enc(&tm, CU_TENSOR_MAP_DATA_TYPE_BFLOAT16, 2, (void*)x, dims, strides, box, es, CU_TENSOR_MAP_INTERLEAVE_NONE,
                   CU_TENSOR_MAP_SWIZZLE_NONE, CU_TENSOR_MAP_L2_PROMOTION_NONE, CU_TENSOR_MAP_FLOAT_OOB_FILL_NONE) == CUDA_SUCCESS;
    }
    if (fast) {
        cudaLaunchAttribute at;
        at.id = cudaLaunchAttributeCooperative; at.val.cooperative = 1;
        cudaLaunchConfig_t cfg = {};
        cfg.gridDim = dim3(NCTA); cfg.blockDim = dim3(NTHREADS); cfg.dynamicSmemBytes = SM_TOTAL;
        cfg.attrs = &at; cfg.numAttrs = 1;
        cudaLaunchKernelEx(&cfg, eca_kernel, tm, w, (const char*)x, (char*)d_out, 0u);
    } else {
        const int rows = in_sizes[0] / CH;
        eca_fb::sum_kernel<<<256, CH>>>(x, rows);
        eca_fb::scale_kernel<<<1024, CH>>>(x, w, (__nv_bfloat16*)d_out, rows);
    }
}
```

```cpp
#include <cuda_runtime.h>
#include <cuda_bf16.h>
#include <cuda.h>
#include <stdint.h>

namespace eca {

constexpr int ROWS = 147456;
constexpr int CH = 384;
constexpr int ROWB = CH * 2;
constexpr int NSTRIP = 3;
constexpr int NCTA = 132;
constexpr int NW = 8;
constexpr int NTHREADS = 384;
constexpr int G = 2;
constexpr int WPG = NW / G;
constexpr int TR = 32;
constexpr int TB = TR * 256;
constexpr int M = 2 * G;
constexpr int NBOX = ROWS / TR;
constexpr int UPS = (NBOX + NCTA - 1) / NCTA;
constexpr int NU = UPS * NSTRIP;
constexpr int NS = 28;
constexpr int NR = 13;
constexpr int NREP = 2;
constexpr int PRE = 4;

constexpr int WIN0 = 8, WIN1 = 6, WIN1_FROM = 42, WIN_END = 50;
constexpr int LD_FROM = 8, LD_END = 64, LD_T = 335, LD_OFF = -1100;
constexpr int LAZY0 = 22, K_E = 2, LAZY = 25, LAZY_UP_AT = 22;
constexpr int T_0 = 1950, T_E = 1100, K_M = 11, T_M = 1240;
constexpr int CREDIT = 1000, STAG = 500, SLACK = 2200;
constexpr int LOOK = 2, T_END = 700, T_COVER = 675, T_LAST = 12600;
constexpr int PF_START = 55, PF_FIRST = 7, PF_TIMED = 10, PF_T = 950, PF_TFAST = 410, PF_D0 = 9, PF_D1 = 3;
static_assert(G == 2 && NS % G == 0 && UPS % 2 == 1, "box u belongs to group u % 2 and slot u % NS");
static_assert(LAZY0 >= (UPS + 1) / G && LAZY >= LAZY0 && LAZY + 1 <= NS / G + NR, "a strip is posted before its scale is awaited; no wait for an unissued box");
static_assert(UPS - 1 + NR < NU / G - LOOK, "refills never overtake the sums");
static_assert(NS + G * NR < 2 * UPS - G, "partial-sum rows and scales are consumed before they are reused");

constexpr int SM_PART = NS * TB;
constexpr int SM_SCALE = SM_PART + 2048;
constexpr int SM_FULL = SM_SCALE + 512;
constexpr int SM_EMPTY = SM_FULL + NS * 8;
constexpr int SM_PBAR = SM_EMPTY + NS * 8;
constexpr int SM_SBAR = SM_PBAR + 8;
constexpr int SM_ISS = SM_SBAR + NSTRIP * 8;
constexpr int SM_TRDY = SM_ISS + 4;
constexpr int SM_TOTAL = SM_ISS + 8;
static_assert(SM_TOTAL <= 232448, "smem");

constexpr int CPB = 8, SUMS = 528, CNTS = 1056;
struct Scratch {
    double sum[NSTRIP * NREP][128 / CPB][SUMS];
    unsigned cnt[NSTRIP][2][CNTS];
    unsigned flag[2][32];
    unsigned epoch[2][NCTA];
};
__device__ __align__(128) Scratch g_s;

__device__ __forceinline__ uint4 lds128(uint32_t a) {
    uint4 v; asm volatile("ld.shared.v4.u32 {%0,%1,%2,%3}, [%4];" : "=r"(v.x), "=r"(v.y), "=r"(v.z), "=r"(v.w) : "r"(a) : "memory"); return v;
}
__device__ __forceinline__ uint32_t ldsv32(uint32_t a) { uint32_t v; asm volatile("ld.volatile.shared.u32 %0, [%1];" : "=r"(v) : "r"(a) : "memory"); return v; }
__device__ __forceinline__ void stsv32(uint32_t a, uint32_t v) { asm volatile("st.volatile.shared.u32 [%0], %1;" :: "r"(a), "r"(v) : "memory"); }
__device__ __forceinline__ void mbar_init(uint32_t bar, uint32_t n) { asm volatile("mbarrier.init.shared::cta.b64 [%0], %1;" :: "r"(bar), "r"(n) : "memory"); }
__device__ __forceinline__ bool mbar_test(uint32_t bar, uint32_t ph) {
    uint32_t ok;
    asm volatile("{\n\t.reg .pred p;\n\tmbarrier.test_wait.parity.shared::cta.b64 p, [%1], %2;\n\tselp.u32 %0, 1, 0, p;\n\t}" : "=r"(ok) : "r"(bar), "r"(ph) : "memory");
    return ok;
}
__device__ __forceinline__ void mbar_wait(uint32_t bar, uint32_t ph) {
    asm volatile("{\n\t.reg .pred p, q;\n\t.reg .u32 n;\n\tmov.u32 n, 0;\n"
                 "W_%=:\n\tmbarrier.try_wait.parity.shared::cta.b64 p, [%0], %1, 1000;\n\t@p bra D_%=;\n\t"
                 "add.u32 n, n, 1;\n\tsetp.lt.u32 q, n, 0x400000;\n\t@q bra W_%=;\n\ttrap;\n"
                 "D_%=:\n\t}" :: "r"(bar), "r"(ph) : "memory");
}
__device__ __forceinline__ void mbar_arrive_elect(uint32_t bar) {
    asm volatile("{\n\t.reg .pred p;\n\telect.sync _|p, 0xffffffff;\n\t@p mbarrier.arrive.shared::cta.b64 _, [%0];\n\t}" :: "r"(bar) : "memory");
}
__device__ __forceinline__ void tma_load(uint32_t dst, const CUtensorMap* tm, uint32_t bar, int c, int r, uint64_t pol) {
    asm volatile("mbarrier.arrive.expect_tx.shared::cta.b64 _, [%0], %1;" :: "r"(bar), "r"(TB) : "memory");
    asm volatile("cp.async.bulk.tensor.2d.shared::cluster.global.mbarrier::complete_tx::bytes.L2::cache_hint [%0], [%1, {%3, %4}], [%2], %5;"
                 :: "r"(dst), "l"(tm), "r"(bar), "r"(c), "r"(r), "l"(pol) : "memory");
}
__device__ __forceinline__ uint32_t hmul2bf(uint32_t a, uint32_t b) { uint32_t d; asm("mul.rn.bf16x2 %0, %1, %2;" : "=r"(d) : "r"(a), "r"(b)); return d; }
__device__ __forceinline__ uint64_t pol_stream() { uint64_t p; asm volatile("createpolicy.fractional.L2::evict_first.b64 %0, 1.0;" : "=l"(p)); return p; }
__device__ __forceinline__ uint32_t lane_now() { uint32_t l; asm volatile("mov.u32 %0, %%laneid;" : "=r"(l)); return l; }
__device__ __forceinline__ unsigned now_ns() { unsigned t; asm volatile("mov.u32 %0, %%globaltimer_lo;" : "=r"(t)); return t; }
__device__ __forceinline__ unsigned unow_ns() { return __shfl_sync(0xffffffffu, now_ns(), 0); }
__device__ __forceinline__ float bf_round(float x) { return __bfloat162float(__float2bfloat16_rn(x)); }

__device__ __forceinline__ int box_row(int s, int j, int cta) { const int r = j * NCTA + cta; return (s ? NBOX - 1 - r : r) * TR; }

__global__ void __launch_bounds__(NTHREADS, 1)
eca_kernel(const __grid_constant__ CUtensorMap tmap, const __nv_bfloat16* __restrict__ w1d,
           const char* __restrict__ xin, char* __restrict__ out, const unsigned zero)
{
    extern __shared__ __align__(1024) char smem[];
    const int warp = __shfl_sync(0xffffffffu, threadIdx.x >> 5, 0), lane = threadIdx.x & 31;
    const uint32_t sbase = (uint32_t)__cvta_generic_to_shared(smem);
    const uint32_t full = sbase + SM_FULL, empty = sbase + SM_EMPTY;
    const int cta = blockIdx.x;

    if (threadIdx.x < 128)
        asm volatile("prefetch.global.L2 [%0];" :: "l"(xin + (uint32_t)((box_row(0, threadIdx.x >> 6, cta) + ((threadIdx.x >> 1) & 31)) * ROWB + (threadIdx.x & 1) * 128)) : "memory");
    if (warp == 8) {
        if (lane == 0) {
            const uint64_t pol = pol_stream();
#pragma unroll
            for (int i = 0; i < PRE; i++) mbar_init(full + i * 8, 1);
            asm volatile("fence.proxy.async.shared::cta;" ::: "memory");
#pragma unroll
            for (int i = 0; i < PRE; i++) tma_load(sbase + i * TB, &tmap, full + i * 8, 0, box_row(0, i, cta), pol);
        }
        __syncwarp();
    } else if (warp == 9) {
        if (lane == 0) { for (int i = PRE; i < NS; i++) mbar_init(full + i * 8, 1); asm volatile("fence.proxy.async.shared::cta;" ::: "memory"); }
        __syncwarp();
    } else if (warp == 10) {
        if (lane == 0) { for (int i = 0; i < NS; i++) mbar_init(empty + i * 8, WPG); }
        __syncwarp();
    } else if (warp == 11) {
        if (lane == 0) {
            mbar_init(sbase + SM_PBAR, NW / 2);
            for (int i = 0; i < NSTRIP; i++) mbar_init(sbase + SM_SBAR + i * 8, 2);
            stsv32(sbase + SM_ISS, PRE);
        }
        __syncwarp();
    }
    __syncthreads();

    if (warp >= NW) {
        asm volatile("setmaxnreg.dec.sync.aligned.u32 24;");
        if (warp == 8) {
            if (lane == 0) {
                const uint64_t pol = pol_stream();
                int slot = PRE, s = 0, j = PRE; uint32_t eph = 1;
                const unsigned t0 = now_ns() + LD_OFF;
                int wslot = 0, wu = 0; uint32_t wph = 0;
#pragma unroll 1
                for (int u = PRE; u < NU; u++) {
                    mbar_wait(empty + slot * 8, eph);
                    if (u < WIN_END) {
                        const int lim = u - (u >= WIN1_FROM ? WIN1 : WIN0);
#pragma unroll 1
                        while (wu <= lim) { mbar_wait(full + wslot * 8, wph); wu++; if (++wslot == NS) { wslot = 0; wph ^= 1; } }
                    }
                    if (u >= LD_FROM && u < LD_END) while ((int)(now_ns() - (t0 + u * LD_T)) < 0) { }
                    tma_load(sbase + slot * TB, &tmap, full + slot * 8, s * 128, box_row(s, j, cta), pol);
                    stsv32(sbase + SM_ISS, u + 1);
                    if (++slot == NS) { slot = 0; eph ^= 1; }
                    if (++j == UPS) { j = 0; s++; }
                }
            }
        } else if (warp == 10) {
            if (lane == 0) {
                int guard = 0;
                while ((int)ldsv32(sbase + SM_ISS) < PF_START) { __nanosleep(20); if (++guard > (1 << 24)) __trap(); }
                unsigned next = now_ns();
#pragma unroll 1
                for (int pos = PF_FIRST; pos < UPS; pos++) {
                    if (pos < PF_FIRST + PF_TIMED) {
                        while ((int)(now_ns() - next) < 0) { }
                        next += (int)ldsv32(sbase + SM_ISS) == PF_START ? PF_TFAST : PF_T;
                    } else {
                        constexpr int A = PF_FIRST + PF_TIMED, L = UPS - 1 - A;
                        const int gate = 2 * UPS + pos - PF_D0 + (2 * (PF_D0 - PF_D1) * (pos - A) + L) / (2 * L);
                        while ((int)ldsv32(sbase + SM_ISS) < gate) { if (++guard > (1 << 26)) __trap(); }
                    }
                    asm volatile("cp.async.bulk.prefetch.tensor.2d.L2.global [%0, {%1, %2}];" :: "l"(&tmap), "r"(256), "r"(box_row(2, pos, cta)) : "memory");
                }
            }
        } else {
            const int hf = warp == 9 ? 0 : 1;
            const unsigned epoch = __shfl_sync(0xffffffffu, *(volatile unsigned*)&g_s.epoch[hf][cta] + 1, 0);
            const float wv = __shfl_sync(0xffffffffu, __bfloat162float(w1d[0]), 0);
            double* sp = &g_s.sum[0][(hf * 64 + lane) / CPB][lane % CPB];
            constexpr int SI = (32 / CPB) * SUMS, SR = (128 / CPB) * SUMS;
            if (cta < NSTRIP * NREP) {
                unsigned long long o0, o1; unsigned o2 = 0;
                asm volatile("atom.relaxed.gpu.global.exch.b64 %0, [%1], 0;" : "=l"(o0) : "l"(sp + cta * SR) : "memory");
                asm volatile("atom.relaxed.gpu.global.exch.b64 %0, [%1], 0;" : "=l"(o1) : "l"(sp + cta * SR + SI) : "memory");
                if (cta < NSTRIP) asm volatile("atom.relaxed.gpu.global.exch.b32 %0, [%1], 0;" : "=r"(o2) : "l"(&g_s.cnt[cta][hf][lane]) : "memory");
                const unsigned done = __reduce_or_sync(0xffffffffu, ((unsigned)(o0 | o1) | o2) & zero);
                asm volatile("st.relaxed.gpu.global.u32 [%0], %1;" :: "l"(&g_s.flag[hf][cta]), "r"(epoch + done) : "memory");
            }
            for (int guard = 0; ; guard++) {
                __nanosleep(1000);
                unsigned f;
                asm volatile("ld.acquire.gpu.global.u32 %0, [%1];" : "=r"(f) : "l"(&g_s.flag[hf][lane % (NSTRIP * NREP)]) : "memory");
                if (__all_sync(0xffffffffu, f == epoch)) break;
                if (guard > (1 << 20)) __trap();
            }
#pragma unroll 1
            for (int s = 0; s < NSTRIP; s++, sp += NREP * SR) {
                mbar_wait(sbase + SM_PBAR, s & 1);
                unsigned dep = 0;
#pragma unroll
                for (int i = 0; i < 2; i++) {
                    const uint32_t pa = sbase + SM_PART + (hf * 64 + i * 32 + lane_now()) * 4;
                    const float p = (__uint_as_float(ldsv32(pa)) + __uint_as_float(ldsv32(pa + 512)))
                                  + (__uint_as_float(ldsv32(pa + 1024)) + __uint_as_float(ldsv32(pa + 1536)));
                    double o;
                    asm volatile("atom.relaxed.gpu.global.add.f64 %0, [%1], %2;" : "=d"(o) : "l"(sp + (cta % NREP) * SR + i * SI), "d"((double)p) : "memory");
                    dep |= (unsigned)__double2loint(o);
                }
                dep = __reduce_or_sync(0xffffffffu, dep & zero);
                {
                    unsigned* cp = &g_s.cnt[s][hf][0];
                    asm volatile("{\n\t.reg .pred p;\n\telect.sync _|p, 0xffffffff;\n\t@p red.relaxed.gpu.global.add.u32 [%0], %1;\n\t}" :: "l"(cp), "r"(dep + 1) : "memory");
                    int guard = 0;
                    while (true) {
                        unsigned c;
                        asm volatile("ld.acquire.gpu.global.u32 %0, [%1];" : "=r"(c) : "l"(cp) : "memory");
                        if (__all_sync(0xffffffffu, c >= NCTA)) break;
                        __nanosleep(50);
                        if (++guard > (1 << 22)) __trap();
                    }
                }
                if (hf == 0) stsv32(sbase + SM_TRDY, now_ns());
                double d[NREP][2];
#pragma unroll
                for (int r = 0; r < NREP; r++)
#pragma unroll
                    for (int i = 0; i < 2; i++)
                        asm volatile("ld.relaxed.gpu.global.f64 %0, [%1];" : "=d"(d[r][i]) : "l"(sp + r * SR + i * SI) : "memory");
#pragma unroll
                for (int i = 0; i < 2; i++) {
                    double t = d[0][i];
#pragma unroll
                    for (int r = 1; r < NREP; r++) t += d[r][i];
                    const float xs = bf_round((float)t), inv = 1.0f / (float)ROWS;
                    const float q0 = xs * inv, q1 = fmaf(fmaf(-q0, (float)ROWS, xs), inv, q0);
                    const float g = bf_round(fabsf(xs) <= 3.4e38f ? q1 : q0);
                    const float z = bf_round(g * wv);
                    float sg; asm("rcp.approx.f32 %0, %1;" : "=f"(sg) : "f"(1.f + expf(-z)));
                    asm volatile("st.shared.u16 [%0], %1;" :: "r"(sbase + SM_SCALE + (s & 1) * 256 + (hf * 64 + i * 32 + lane_now()) * 2), "h"(__bfloat16_as_ushort(__float2bfloat16_rn(sg))) : "memory");
                }
                const uint32_t rb = ldsv32(sbase + SM_SCALE + (s & 1) * 256 + hf * 128 + 64) & zero;
                __syncwarp();
                mbar_arrive_elect(sbase + SM_SBAR + s * 8 + rb);
            }
            if (lane_now() == 0) g_s.epoch[hf][cta] = epoch;
        }
    } else {
        asm volatile("setmaxnreg.inc.sync.aligned.u32 240;");
        const uint64_t pol = pol_stream();
        const int grp = warp / WPG;
        float acc[8];
#pragma unroll
        for (int i = 0; i < 8; i++) acc[i] = 0.f;
        uint4 scl = make_uint4(0, 0, 0, 0);
        uint4 regs[NR][M];
        const int n = (NU + 1 - grp) / G;
        int sum_q = 0, sum_slot = grp, sum_end = (UPS + 1 - grp) / G; uint32_t sum_ph = 0;
        int ref_slot = grp, ri = 0, st_s = 0, st_j = grp, wait_k = 0, mode = 0;
        unsigned tnext = 0, tper = 0;
        const uint32_t lbase = sbase + (warp % WPG) * (M * 512) + lane * 16;
        const uint32_t ooff = ((warp % WPG) * 2 * M + (lane >> 4)) * ROWB + (lane & 15) * 16;

#pragma unroll 1
        for (int k = -NR; k < n; k++) {
            const int need = k + (k < 0 ? NR + 1 : k < K_E ? LAZY0 : k < LAZY_UP_AT ? LAZY : LAZY + 1);
            while (sum_q < n) {
                if (k > 0 && k < UPS) {
                    bool go;
                    do {
                        if (!mode && sum_q >= need && (int)(unow_ns() - tnext) >= 0) { go = false; break; }
                        go = __any_sync(0xffffffffu, mbar_test(full + sum_slot * 8, sum_ph));
                    } while (!go && !(mode && (int)(unow_ns() - tnext) >= 0));
                    if (!go) break;
                } else if (sum_q >= need) break;
                mbar_wait(full + sum_slot * 8, sum_ph);
                const uint32_t a = lbase + sum_slot * TB;
#pragma unroll
                for (int i = 0; i < M; i++) {
                    const uint4 v = lds128(a + i * 512);
                    acc[0] += __uint_as_float(v.x << 16); acc[1] += __uint_as_float(v.x & 0xffff0000u);
                    acc[2] += __uint_as_float(v.y << 16); acc[3] += __uint_as_float(v.y & 0xffff0000u);
                    acc[4] += __uint_as_float(v.z << 16); acc[5] += __uint_as_float(v.z & 0xffff0000u);
                    acc[6] += __uint_as_float(v.w << 16); acc[7] += __uint_as_float(v.w & 0xffff0000u);
                }
                sum_q++; sum_slot += G; if (sum_slot >= NS) { sum_slot -= NS; sum_ph ^= 1; }
                if (sum_q == n - LOOK) { mode = 1; tnext = unow_ns(); tper = T_END; }
                if (sum_q == sum_end) {
                    const uint32_t ln = lane_now();
                    const bool hi = ln >= 16;
                    const uint32_t pa = sbase + SM_PART + (warp >> 1) * 512 + (ln & 15) * 32 + (ln & 16);
                    float r[4];
#pragma unroll
                    for (int i = 0; i < 4; i++) r[i] = (hi ? acc[4 + i] : acc[i]) + __shfl_xor_sync(0xffffffffu, hi ? acc[i] : acc[4 + i], 16);
                    if (!(warp & 1)) {
                        asm volatile("barrier.sync %0, 64;" :: "r"(1 + (warp >> 1)) : "memory");
                        const uint4 o = lds128(pa);
                        r[0] += __uint_as_float(o.x); r[1] += __uint_as_float(o.y); r[2] += __uint_as_float(o.z); r[3] += __uint_as_float(o.w);
                    }
                    asm volatile("st.shared.v4.f32 [%0], {%1,%2,%3,%4};" :: "r"(pa), "f"(r[0]), "f"(r[1]), "f"(r[2]), "f"(r[3]) : "memory");
                    const uint32_t rb = __shfl_sync(0xffffffffu, ldsv32(pa) & zero, 0);
                    if (warp & 1) asm volatile("barrier.arrive %0, 64;" :: "r"(1 + (warp >> 1) + rb) : "memory");
                    else mbar_arrive_elect(sbase + SM_PBAR + rb);
#pragma unroll
                    for (int i = 0; i < 8; i++) acc[i] = 0.f;
                    if (sum_q == n) tper = T_COVER;
                    sum_end = sum_end < UPS ? UPS : n;
                }
            }
            if (k == wait_k) {
                mbar_wait(sbase + SM_SBAR + st_s * 8, 0);
                scl = lds128(sbase + SM_SCALE + (st_s & 1) * 256 + (lane_now() & 15) * 16);
                wait_k = k == 0 ? (UPS + 1 - grp) / G : UPS;
            }
            if (mode == 1 && __any_sync(0xffffffffu, mbar_test(sbase + SM_SBAR + (NSTRIP - 1) * 8, 0))) {
                mode = 2;
                const unsigned now = unow_ns();
                if ((int)(now - tnext) > 0) tnext = now;
                const int left = (int)(ldsv32(sbase + SM_TRDY) + T_LAST - tnext);
                tper = __shfl_sync(0xffffffffu, (unsigned)__fdividef((float)(left > 0 ? left : 0), (float)(n - k)), 0);
            }
            if (mode) { while ((int)(now_ns() - tnext) < 0) { } tnext += tper; }
            else if (k >= 0) {
                const unsigned lo = unow_ns() - SLACK;
                if (k == 0) tnext = lo + (SLACK - CREDIT) + grp * STAG; else if ((int)(lo - tnext) > 0) tnext = lo;
                tnext += k >= K_M ? T_M : k >= K_E ? T_E : T_0;
            }
            const int row = box_row(st_s, st_j, cta);
            const bool do_ld = k + NR < n, do_st = k >= 0 && (unsigned)row < (unsigned)ROWS;
            char* const op = out + ((uint32_t)(row * ROWB + st_s * 256) + ooff);
            if (k >= 0) { st_j += G; if (st_j >= UPS) { st_j -= UPS; st_s++; } }
            const uint32_t a = lbase + ref_slot * TB;
            uint32_t dep = 0;
#define ECA_CASE(K) case K: \
                if (do_st) { _Pragma("unroll") for (int i = 0; i < M; i++) { \
                    uint4& v = regs[K][i]; \
                    v.x = hmul2bf(v.x, scl.x); v.y = hmul2bf(v.y, scl.y); v.z = hmul2bf(v.z, scl.z); v.w = hmul2bf(v.w, scl.w); \
                    asm volatile("st.global.L2::cache_hint.v4.u32 [%0], {%1,%2,%3,%4}, %5;" \
                                 :: "l"(op + i * 2 * ROWB), "r"(v.x), "r"(v.y), "r"(v.z), "r"(v.w), "l"(pol) : "memory"); } } \
                if (do_ld) { _Pragma("unroll") for (int i = 0; i < M; i++) { regs[K][i] = lds128(a + i * 512); dep |= regs[K][i].x; } } \
                break;
            static_assert(NR == 13, "one case per register set");
            switch (ri) {
                ECA_CASE(0) ECA_CASE(1) ECA_CASE(2) ECA_CASE(3) ECA_CASE(4) ECA_CASE(5) ECA_CASE(6)
                ECA_CASE(7) ECA_CASE(8) ECA_CASE(9) ECA_CASE(10) ECA_CASE(11) ECA_CASE(12)
                default: break;
            }
#undef ECA_CASE
            if (k + NR + NS / G < n) { __syncwarp(); mbar_arrive_elect(empty + ref_slot * 8 + (dep & zero)); }
            if (++ri == NR) ri = 0;
            ref_slot += G; if (ref_slot >= NS) ref_slot -= NS;
        }
    }
}

}

namespace eca_fb {
__device__ float g_part[256][eca::CH];
__global__ void sum_kernel(const __nv_bfloat16* __restrict__ x, int rows) {
    const int c = threadIdx.x; float a = 0.f;
    for (int r = blockIdx.x; r < rows; r += gridDim.x) a += __bfloat162float(x[(size_t)r * eca::CH + c]);
    g_part[blockIdx.x][c] = a;
}
__global__ void scale_kernel(const __nv_bfloat16* __restrict__ x, const __nv_bfloat16* __restrict__ w, __nv_bfloat16* __restrict__ y, int rows) {
    const int c = threadIdx.x; double t = 0.0;
    for (int i = 0; i < 256; i++) t += g_part[i][c];
    const float g = eca::bf_round(eca::bf_round((float)t) / (float)rows);
    const float z = eca::bf_round(g * __bfloat162float(w[0]));
    const __nv_bfloat16 s = __float2bfloat16_rn(1.f / (1.f + expf(-z)));
    for (int r = blockIdx.x; r < rows; r += gridDim.x) y[(size_t)r * eca::CH + c] = __hmul(x[(size_t)r * eca::CH + c], s);
}
}

typedef CUresult (*EncodeFn)(CUtensorMap*, CUtensorMapDataType, cuuint32_t, void*, const cuuint64_t*, const cuuint64_t*,
                             const cuuint32_t*, const cuuint32_t*, CUtensorMapInterleave, CUtensorMapSwizzle,
                             CUtensorMapL2promotion, CUtensorMapFloatOOBfill);

extern "C" void kernel_launch(void* const* d_in, const int* in_sizes, int n_in, void* d_out, int out_size) {
    using namespace eca;
    const __nv_bfloat16* x = (const __nv_bfloat16*)d_in[0];
    const __nv_bfloat16* w = (const __nv_bfloat16*)d_in[1];
    static int mode = -1;
    static EncodeFn enc = nullptr;
    if (mode < 0) {
        int dev = 0, sms = 0, occ = 0;
        cudaGetDevice(&dev);
        cudaDeviceGetAttribute(&sms, cudaDevAttrMultiProcessorCount, dev);
        cudaDriverEntryPointQueryResult q;
        cudaGetDriverEntryPoint("cuTensorMapEncodeTiled", (void**)&enc, cudaEnableDefault, &q);
        cudaError_t e = cudaFuncSetAttribute(eca_kernel, cudaFuncAttributeMaxDynamicSharedMemorySize, SM_TOTAL);
        if (e == cudaSuccess) e = cudaOccupancyMaxActiveBlocksPerMultiprocessor(&occ, eca_kernel, NTHREADS, SM_TOTAL);
        mode = (e == cudaSuccess && enc && sms * occ >= NCTA) ? 1 : 0;
        (void)cudaGetLastError();
    }
    CUtensorMap tm;
    bool fast = mode == 1 && in_sizes[0] == ROWS * CH && out_size == ROWS * CH;
    if (fast) {
        cuuint64_t dims[2] = {(cuuint64_t)CH, (cuuint64_t)ROWS}; cuuint64_t strides[1] = {(cuuint64_t)ROWB};
        cuuint32_t box[2] = {128, (cuuint32_t)TR}; cuuint32_t es[2] = {1, 1};
        fast = enc(&tm, CU_TENSOR_MAP_DATA_TYPE_BFLOAT16, 2, (void*)x, dims, strides, box, es, CU_TENSOR_MAP_INTERLEAVE_NONE,
                   CU_TENSOR_MAP_SWIZZLE_NONE, CU_TENSOR_MAP_L2_PROMOTION_NONE, CU_TENSOR_MAP_FLOAT_OOB_FILL_NONE) == CUDA_SUCCESS;
    }
    if (fast) {
        cudaLaunchAttribute at;
        at.id = cudaLaunchAttributeCooperative; at.val.cooperative = 1;
        cudaLaunchConfig_t cfg = {};
        cfg.gridDim = dim3(NCTA); cfg.blockDim = dim3(NTHREADS); cfg.dynamicSmemBytes = SM_TOTAL;
        cfg.attrs = &at; cfg.numAttrs = 1;
        cudaLaunchKernelEx(&cfg, eca_kernel, tm, w, (const char*)x, (char*)d_out, 0u);
    } else {
        const int rows = in_sizes[0] / CH;
        eca_fb::sum_kernel<<<256, CH>>>(x, rows);
        eca_fb::scale_kernel<<<1024, CH>>>(x, w, (__nv_bfloat16*)d_out, rows);
    }
}
```

```cpp
#include <cuda_runtime.h>
#include <cuda_bf16.h>
#include <cuda.h>
#include <stdint.h>

namespace eca {

constexpr int ROWS = 147456;
constexpr int CH = 384;
constexpr int ROWB = CH * 2;
constexpr int NSTRIP = 3;
constexpr int NCTA = 132;
constexpr int NW = 8;
constexpr int NTHREADS = 384;
constexpr int G = 2;
constexpr int WPG = NW / G;
constexpr int TR = 32;
constexpr int TB = TR * 256;
constexpr int M = 2 * G;
constexpr int NBOX = ROWS / TR;
constexpr int UPS = (NBOX + NCTA - 1) / NCTA;
constexpr int NU = UPS * NSTRIP;
constexpr int NS = 28;
constexpr int NR = 13;
constexpr int NREP = 2;
constexpr int PRE = 4;

constexpr int WIN0 = 9, WIN1 = 6, WIN1_FROM = 42, WIN_END = 50;
constexpr int LD_FROM = 8, LD_END = 62, LD_T = 331, LD_LEAD = 950;
constexpr int LAZY0 = 23, K_E = 2, LAZY = 24, LAZY_UP_AT = 20;
constexpr int T_0 = 1450, T_E = 1120, K_M = 10, T_M = 1220;
constexpr int CREDIT = 680, STAG = 500, SLACK = 1000;
constexpr int K_LEVEL = (UPS + 1) / G, T_LEVEL = 9100;
constexpr int LOOK = 2, T_END = 720, T_COVER = 665, T_LAST = 15370;
constexpr int PF_START = 53, PF_FIRST = 7, PF_TIMED = 10, PF_T = 1020, PF_TFAST = 290, PF_D0 = 9, PF_D1 = 3;
static_assert(NCTA < 256 && G == 2 && NS % G == 0 && UPS % 2 == 1, "box u belongs to group u % 2 and slot u % NS");
static_assert(LAZY0 >= (UPS + 1) / G && LAZY >= LAZY0 && LAZY + 1 <= NS / G + NR, "a strip is posted before its scale is awaited; no wait for an unissued box");
static_assert(UPS - 1 + NR < NU / G - LOOK, "refills never overtake the sums");
static_assert(NS + G * NR < 2 * UPS - G, "partial-sum rows and scales are consumed before they are reused");

constexpr int SM_PART = NS * TB;
constexpr int SM_SCALE = SM_PART + 2048;
constexpr int SM_FULL = SM_SCALE + 512;
constexpr int SM_EMPTY = SM_FULL + NS * 8;
constexpr int SM_PBAR = SM_EMPTY + NS * 8;
constexpr int SM_SBAR = SM_PBAR + 8;
constexpr int SM_ISS = SM_SBAR + NSTRIP * 8;
constexpr int SM_TAVG = SM_ISS + 4;
constexpr int SM_TOTAL = SM_ISS + 8;
static_assert(SM_TOTAL <= 232448, "smem");

constexpr int CPB = 8, SUMS = 528, CNTS = 1056;
struct Scratch {
    double sum[NSTRIP * NREP][128 / CPB][SUMS];
    unsigned cnt[NSTRIP][2][CNTS];
    unsigned flag[2][32];
    unsigned epoch[2][NCTA];
};
__device__ __align__(128) Scratch g_s;

__device__ __forceinline__ uint4 lds128(uint32_t a) {
    uint4 v; asm volatile("ld.shared.v4.u32 {%0,%1,%2,%3}, [%4];" : "=r"(v.x), "=r"(v.y), "=r"(v.z), "=r"(v.w) : "r"(a) : "memory"); return v;
}
__device__ __forceinline__ uint32_t ldsv32(uint32_t a) { uint32_t v; asm volatile("ld.volatile.shared.u32 %0, [%1];" : "=r"(v) : "r"(a) : "memory"); return v; }
__device__ __forceinline__ void stsv32(uint32_t a, uint32_t v) { asm volatile("st.volatile.shared.u32 [%0], %1;" :: "r"(a), "r"(v) : "memory"); }
__device__ __forceinline__ void mbar_init(uint32_t bar, uint32_t n) { asm volatile("mbarrier.init.shared::cta.b64 [%0], %1;" :: "r"(bar), "r"(n) : "memory"); }
__device__ __forceinline__ bool mbar_test(uint32_t bar, uint32_t ph) {
    uint32_t ok;
    asm volatile("{\n\t.reg .pred p;\n\tmbarrier.test_wait.parity.shared::cta.b64 p, [%1], %2;\n\tselp.u32 %0, 1, 0, p;\n\t}" : "=r"(ok) : "r"(bar), "r"(ph) : "memory");
    return ok;
}
__device__ __forceinline__ void mbar_wait(uint32_t bar, uint32_t ph) {
    asm volatile("{\n\t.reg .pred p, q;\n\t.reg .u32 n;\n\tmov.u32 n, 0;\n"
                 "W_%=:\n\tmbarrier.try_wait.parity.shared::cta.b64 p, [%0], %1, 1000;\n\t@p bra D_%=;\n\t"
                 "add.u32 n, n, 1;\n\tsetp.lt.u32 q, n, 0x400000;\n\t@q bra W_%=;\n\ttrap;\n"
                 "D_%=:\n\t}" :: "r"(bar), "r"(ph) : "memory");
}
__device__ __forceinline__ void mbar_arrive_elect(uint32_t bar) {
    asm volatile("{\n\t.reg .pred p;\n\telect.sync _|p, 0xffffffff;\n\t@p mbarrier.arrive.shared::cta.b64 _, [%0];\n\t}" :: "r"(bar) : "memory");
}
__device__ __forceinline__ void tma_load(uint32_t dst, const CUtensorMap* tm, uint32_t bar, int c, int r, uint64_t pol) {
    asm volatile("mbarrier.arrive.expect_tx.shared::cta.b64 _, [%0], %1;" :: "r"(bar), "r"(TB) : "memory");
    asm volatile("cp.async.bulk.tensor.2d.shared::cluster.global.mbarrier::complete_tx::bytes.L2::cache_hint [%0], [%1, {%3, %4}], [%2], %5;"
                 :: "r"(dst), "l"(tm), "r"(bar), "r"(c), "r"(r), "l"(pol) : "memory");
}
__device__ __forceinline__ uint32_t hmul2bf(uint32_t a, uint32_t b) { uint32_t d; asm("mul.rn.bf16x2 %0, %1, %2;" : "=r"(d) : "r"(a), "r"(b)); return d; }
__device__ __forceinline__ uint64_t pol_stream() { uint64_t p; asm volatile("createpolicy.fractional.L2::evict_first.b64 %0, 1.0;" : "=l"(p)); return p; }
__device__ __forceinline__ uint32_t lane_now() { uint32_t l; asm volatile("mov.u32 %0, %%laneid;" : "=r"(l)); return l; }
__device__ __forceinline__ unsigned now_ns() { unsigned t; asm volatile("mov.u32 %0, %%globaltimer_lo;" : "=r"(t)); return t; }
__device__ __forceinline__ unsigned unow_ns() { return __shfl_sync(0xffffffffu, now_ns(), 0); }
__device__ __forceinline__ float bf_round(float x) { return __bfloat162float(__float2bfloat16_rn(x)); }

__device__ __forceinline__ int box_row(int s, int j, int cta) { const int r = j * NCTA + cta; return (s ? NBOX - 1 - r : r) * TR; }

__global__ void __launch_bounds__(NTHREADS, 1)
eca_kernel(const __grid_constant__ CUtensorMap tmap, const __nv_bfloat16* __restrict__ w1d,
           const char* __restrict__ xin, char* __restrict__ out, const unsigned zero)
{
    extern __shared__ __align__(1024) char smem[];
    const int warp = __shfl_sync(0xffffffffu, threadIdx.x >> 5, 0), lane = threadIdx.x & 31;
    const uint32_t sbase = (uint32_t)__cvta_generic_to_shared(smem);
    const uint32_t full = sbase + SM_FULL, empty = sbase + SM_EMPTY;
    const int cta = blockIdx.x;

    if (threadIdx.x < 128)
        asm volatile("prefetch.global.L2 [%0];" :: "l"(xin + (uint32_t)((box_row(0, threadIdx.x >> 6, cta) + ((threadIdx.x >> 1) & 31)) * ROWB + (threadIdx.x & 1) * 128)) : "memory");
    else if (cta < 8 && threadIdx.x < 128 + ROWS * ROWB / 2097152)
        asm volatile("prefetch.global.L2 [%0];" :: "l"(xin + (threadIdx.x - 128) * 2097152u) : "memory");
    if (warp == 8) {
        if (lane == 0) {
            const uint64_t pol = pol_stream();
#pragma unroll
            for (int i = 0; i < PRE; i++) mbar_init(full + i * 8, 1);
            asm volatile("fence.proxy.async.shared::cta;" ::: "memory");
#pragma unroll
            for (int i = 0; i < PRE; i++) tma_load(sbase + i * TB, &tmap, full + i * 8, 0, box_row(0, i, cta), pol);
        }
        __syncwarp();
    } else if (warp == 9) {
        if (lane == 0) { for (int i = PRE; i < NS; i++) mbar_init(full + i * 8, 1); asm volatile("fence.proxy.async.shared::cta;" ::: "memory"); }
        __syncwarp();
    } else if (warp == 10) {
        if (lane == 0) { for (int i = 0; i < NS; i++) mbar_init(empty + i * 8, WPG); }
        __syncwarp();
    } else if (warp == 11) {
        if (lane == 0) {
            mbar_init(sbase + SM_PBAR, NW / 2);
            for (int i = 0; i < NSTRIP; i++) mbar_init(sbase + SM_SBAR + i * 8, 2);
            stsv32(sbase + SM_ISS, PRE);
        }
        __syncwarp();
    }
    __syncthreads();

    if (warp >= NW) {
        asm volatile("setmaxnreg.dec.sync.aligned.u32 24;");
        if (warp == 8) {
            if (lane == 0) {
                const uint64_t pol = pol_stream();
                int slot = PRE, s = 0, j = PRE; uint32_t eph = 1;
                const unsigned t0 = now_ns() - LD_LEAD;
                int wslot = 0, wu = 0; uint32_t wph = 0;
#pragma unroll 1
                for (int u = PRE; u < NU; u++) {
                    mbar_wait(empty + slot * 8, eph);
                    if (u < WIN_END) {
                        const int lim = u - (u >= WIN1_FROM ? WIN1 : WIN0);
#pragma unroll 1
                        while (wu <= lim) { mbar_wait(full + wslot * 8, wph); wu++; if (++wslot == NS) { wslot = 0; wph ^= 1; } }
                    }
                    if (u >= LD_FROM && u < LD_END) while ((int)(now_ns() - (t0 + u * LD_T)) < 0) { }
                    tma_load(sbase + slot * TB, &tmap, full + slot * 8, s * 128, box_row(s, j, cta), pol);
                    stsv32(sbase + SM_ISS, u + 1);
                    if (++slot == NS) { slot = 0; eph ^= 1; }
                    if (++j == UPS) { j = 0; s++; }
                }
            }
        } else if (warp == 10) {
            if (lane == 0) {
                int guard = 0;
                while ((int)ldsv32(sbase + SM_ISS) < PF_START) { __nanosleep(20); if (++guard > (1 << 24)) __trap(); }
                unsigned next = now_ns();
#pragma unroll 1
                for (int pos = PF_FIRST; pos < UPS; pos++) {
                    if (pos < PF_FIRST + PF_TIMED) {
                        while ((int)(now_ns() - next) < 0) { }
                        next += (int)ldsv32(sbase + SM_ISS) == PF_START ? PF_TFAST : PF_T;
                    } else {
                        constexpr int A = PF_FIRST + PF_TIMED, L = UPS - 1 - A;
                        const int gate = 2 * UPS + pos - PF_D0 + (2 * (PF_D0 - PF_D1) * (pos - A) + L) / (2 * L);
                        while ((int)ldsv32(sbase + SM_ISS) < gate) { if (++guard > (1 << 26)) __trap(); }
                    }
                    asm volatile("cp.async.bulk.prefetch.tensor.2d.L2.global [%0, {%1, %2}];" :: "l"(&tmap), "r"(256), "r"(box_row(2, pos, cta)) : "memory");
                }
            }
        } else {
            const int hf = warp == 9 ? 0 : 1;
            const unsigned epoch = __shfl_sync(0xffffffffu, *(volatile unsigned*)&g_s.epoch[hf][cta] + 1, 0);
            const float wv = __shfl_sync(0xffffffffu, __bfloat162float(w1d[0]), 0);
            double* sp = &g_s.sum[0][(hf * 64 + lane) / CPB][lane % CPB];
            constexpr int SI = (32 / CPB) * SUMS, SR = (128 / CPB) * SUMS;
            if (cta < NSTRIP * NREP) {
                unsigned long long o0, o1; unsigned o2 = 0;
                asm volatile("atom.relaxed.gpu.global.exch.b64 %0, [%1], 0;" : "=l"(o0) : "l"(sp + cta * SR) : "memory");
                asm volatile("atom.relaxed.gpu.global.exch.b64 %0, [%1], 0;" : "=l"(o1) : "l"(sp + cta * SR + SI) : "memory");
                if (cta < NSTRIP) asm volatile("atom.relaxed.gpu.global.exch.b32 %0, [%1], 0;" : "=r"(o2) : "l"(&g_s.cnt[cta][hf][lane]) : "memory");
                const unsigned done = __reduce_or_sync(0xffffffffu, ((unsigned)(o0 | o1) | o2) & zero);
                asm volatile("st.relaxed.gpu.global.u32 [%0], %1;" :: "l"(&g_s.flag[hf][cta]), "r"(epoch + done) : "memory");
            }
            for (int guard = 0; ; guard++) {
                __nanosleep(1000);
                unsigned f;
                asm volatile("ld.acquire.gpu.global.u32 %0, [%1];" : "=r"(f) : "l"(&g_s.flag[hf][lane % (NSTRIP * NREP)]) : "memory");
                if (__all_sync(0xffffffffu, f == epoch)) break;
                if (guard > (1 << 20)) __trap();
            }
#pragma unroll 1
            for (int s = 0; s < NSTRIP; s++, sp += NREP * SR) {
                mbar_wait(sbase + SM_PBAR, s & 1);
                const unsigned ta = unow_ns();
                unsigned dep = 0;
#pragma unroll
                for (int i = 0; i < 2; i++) {
                    const uint32_t pa = sbase + SM_PART + (hf * 64 + i * 32 + lane_now()) * 4;
                    const float p = (__uint_as_float(ldsv32(pa)) + __uint_as_float(ldsv32(pa + 512)))
                                  + (__uint_as_float(ldsv32(pa + 1024)) + __uint_as_float(ldsv32(pa + 1536)));
                    double o;
                    asm volatile("atom.relaxed.gpu.global.add.f64 %0, [%1], %2;" : "=d"(o) : "l"(sp + (cta % NREP) * SR + i * SI), "d"((double)p) : "memory");
                    dep |= (unsigned)__double2loint(o);
                }
                dep = __reduce_or_sync(0xffffffffu, dep & zero);
                {
                    unsigned* cp = &g_s.cnt[s][hf][0];
                    asm volatile("{\n\t.reg .pred p;\n\telect.sync _|p, 0xffffffff;\n\t@p red.relaxed.gpu.global.add.u32 [%0], %1;\n\t}" :: "l"(cp), "r"(dep + 1 + ((ta >> 5) << 8)) : "memory");
                    int guard = 0;
                    while (true) {
                        asm volatile("ld.acquire.gpu.global.u32 %0, [%1];" : "=r"(dep) : "l"(cp) : "memory");
                        if (__all_sync(0xffffffffu, (dep & 255u) == NCTA)) break;
                        __nanosleep(50);
                        if (++guard > (1 << 22)) __trap();
                    }
                }
                if (hf == 0) {
                    const unsigned now = now_ns();
                    stsv32(sbase + SM_TAVG, now - (((now >> 5) * NCTA - (dep >> 8)) & 0xffffffu) * 32u / NCTA);
                }
                double d[NREP][2];
#pragma unroll
                for (int r = 0; r < NREP; r++)
#pragma unroll
                    for (int i = 0; i < 2; i++)
                        asm volatile("ld.relaxed.gpu.global.f64 %0, [%1];" : "=d"(d[r][i]) : "l"(sp + r * SR + i * SI) : "memory");
#pragma unroll
                for (int i = 0; i < 2; i++) {
                    double t = d[0][i];
#pragma unroll
                    for (int r = 1; r < NREP; r++) t += d[r][i];
                    const float xs = bf_round((float)t), inv = 1.0f / (float)ROWS;
                    const float q0 = xs * inv, q1 = fmaf(fmaf(-q0, (float)ROWS, xs), inv, q0);
                    const float g = bf_round(fabsf(xs) <= 3.4e38f ? q1 : q0);
                    const float z = bf_round(g * wv);
                    float sg; asm("rcp.approx.f32 %0, %1;" : "=f"(sg) : "f"(1.f + expf(-z)));
                    asm volatile("st.shared.u16 [%0], %1;" :: "r"(sbase + SM_SCALE + (s & 1) * 256 + (hf * 64 + i * 32 + lane_now()) * 2), "h"(__bfloat16_as_ushort(__float2bfloat16_rn(sg))) : "memory");
                }
                const uint32_t rb = ldsv32(sbase + SM_SCALE + (s & 1) * 256 + hf * 128 + 64) & zero;
                __syncwarp();
                mbar_arrive_elect(sbase + SM_SBAR + s * 8 + rb);
            }
            if (lane_now() == 0) g_s.epoch[hf][cta] = epoch;
        }
    } else {
        asm volatile("setmaxnreg.inc.sync.aligned.u32 240;");
        const uint64_t pol = pol_stream();
        const int grp = warp / WPG;
        float acc[8];
#pragma unroll
        for (int i = 0; i < 8; i++) acc[i] = 0.f;
        uint4 scl = make_uint4(0, 0, 0, 0);
        uint4 regs[NR][M];
        const int n = (NU + 1 - grp) / G;
        int sum_q = 0, sum_slot = grp, sum_end = (UPS + 1 - grp) / G; uint32_t sum_ph = 0;
        int ref_slot = grp, ri = 0, st_s = 0, st_j = grp, wait_k = 0, mode = 0;
        unsigned tnext = 0, tper = 0;
        const uint32_t lbase = sbase + (warp % WPG) * (M * 512) + lane * 16;
        const uint32_t ooff = ((warp % WPG) * 2 * M + (lane >> 4)) * ROWB + (lane & 15) * 16;

#pragma unroll 1
        for (int k = -NR; k < n; k++) {
            const int need = k + (k < 0 ? NR + 1 : k < K_E ? LAZY0 : k < LAZY_UP_AT ? LAZY : LAZY + 1);
            while (sum_q < n) {
                if (k > 0 && k < UPS) {
                    bool go;
                    do {
                        if (!mode && sum_q >= need && (int)(unow_ns() - tnext) >= 0) { go = false; break; }
                        go = __any_sync(0xffffffffu, mbar_test(full + sum_slot * 8, sum_ph));
                    } while (!go && !(mode && (int)(unow_ns() - tnext) >= 0));
                    if (!go) break;
                } else if (sum_q >= need) break;
                mbar_wait(full + sum_slot * 8, sum_ph);
                const uint32_t a = lbase + sum_slot * TB;
#pragma unroll
                for (int i = 0; i < M; i++) {
                    const uint4 v = lds128(a + i * 512);
                    acc[0] += __uint_as_float(v.x << 16); acc[1] += __uint_as_float(v.x & 0xffff0000u);
                    acc[2] += __uint_as_float(v.y << 16); acc[3] += __uint_as_float(v.y & 0xffff0000u);
                    acc[4] += __uint_as_float(v.z << 16); acc[5] += __uint_as_float(v.z & 0xffff0000u);
                    acc[6] += __uint_as_float(v.w << 16); acc[7] += __uint_as_float(v.w & 0xffff0000u);
                }
                sum_q++; sum_slot += G; if (sum_slot >= NS) { sum_slot -= NS; sum_ph ^= 1; }
                if (sum_q == n - LOOK) { mode = 1; tnext = unow_ns(); tper = T_END; }
                if (sum_q == sum_end) {
                    const uint32_t ln = lane_now();
                    const bool hi = ln >= 16;
                    const uint32_t pa = sbase + SM_PART + (warp >> 1) * 512 + (ln & 15) * 32 + (ln & 16);
                    float r[4];
#pragma unroll
                    for (int i = 0; i < 4; i++) r[i] = (hi ? acc[4 + i] : acc[i]) + __shfl_xor_sync(0xffffffffu, hi ? acc[i] : acc[4 + i], 16);
                    if (!(warp & 1)) {
                        asm volatile("barrier.sync %0, 64;" :: "r"(1 + (warp >> 1)) : "memory");
                        const uint4 o = lds128(pa);
                        r[0] += __uint_as_float(o.x); r[1] += __uint_as_float(o.y); r[2] += __uint_as_float(o.z); r[3] += __uint_as_float(o.w);
                    }
                    asm volatile("st.shared.v4.f32 [%0], {%1,%2,%3,%4};" :: "r"(pa), "f"(r[0]), "f"(r[1]), "f"(r[2]), "f"(r[3]) : "memory");
                    const uint32_t rb = __shfl_sync(0xffffffffu, ldsv32(pa) & zero, 0);
                    if (warp & 1) asm volatile("barrier.arrive %0, 64;" :: "r"(1 + (warp >> 1) + rb) : "memory");
                    else mbar_arrive_elect(sbase + SM_PBAR + rb);
#pragma unroll
                    for (int i = 0; i < 8; i++) acc[i] = 0.f;
                    if (sum_q == n) tper = T_COVER;
                    sum_end = sum_end < UPS ? UPS : n;
                }
            }
            if (k == wait_k) {
                mbar_wait(sbase + SM_SBAR + st_s * 8, 0);
                scl = lds128(sbase + SM_SCALE + (st_s & 1) * 256 + (lane_now() & 15) * 16);
                wait_k = k == 0 ? (UPS + 1 - grp) / G : UPS;
            }
            if (mode == 1 && __any_sync(0xffffffffu, mbar_test(sbase + SM_SBAR + (NSTRIP - 1) * 8, 0))) {
                mode = 2;
                const unsigned now = unow_ns();
                if ((int)(now - tnext) > 0) tnext = now;
                const int left = (int)(ldsv32(sbase + SM_TAVG) + T_LAST - tnext);
                tper = __shfl_sync(0xffffffffu, (unsigned)__fdividef((float)(left > 0 ? left : 0), (float)(n - k)), 0);
            }
            if (mode) { while ((int)(now_ns() - tnext) < 0) { } tnext += tper; }
            else if (k >= 0) {
                if (k == K_LEVEL)
                    tnext += (int)(__shfl_sync(0xffffffffu, ldsv32(sbase + SM_TAVG), 0) + T_LEVEL + grp * STAG - tnext) * 3 / 4;
                const unsigned lo = unow_ns() - SLACK;
                if (k == 0) tnext = lo + (SLACK - CREDIT) + grp * STAG; else if ((int)(lo - tnext) > 0) tnext = lo;
                tnext += k >= K_M ? T_M : k >= K_E ? T_E : T_0;
            }
            const int row = box_row(st_s, st_j, cta);
            const bool do_ld = k + NR < n, do_st = k >= 0 && (unsigned)row < (unsigned)ROWS;
            char* const op = out + ((uint32_t)(row * ROWB + st_s * 256) + ooff);
            if (k >= 0) { st_j += G; if (st_j >= UPS) { st_j -= UPS; st_s++; } }
            const uint32_t a = lbase + ref_slot * TB;
            uint32_t dep = 0;
#define ECA_CASE(K) case K: \
                if (do_st) { _Pragma("unroll") for (int i = 0; i < M; i++) { \
                    uint4& v = regs[K][i]; \
                    v.x = hmul2bf(v.x, scl.x); v.y = hmul2bf(v.y, scl.y); v.z = hmul2bf(v.z, scl.z); v.w = hmul2bf(v.w, scl.w); \
                    asm volatile("st.global.L2::cache_hint.v4.u32 [%0], {%1,%2,%3,%4}, %5;" \
                                 :: "l"(op + i * 2 * ROWB), "r"(v.x), "r"(v.y), "r"(v.z), "r"(v.w), "l"(pol) : "memory"); } } \
                if (do_ld) { _Pragma("unroll") for (int i = 0; i < M; i++) { regs[K][i] = lds128(a + i * 512); dep |= regs[K][i].x; } } \
                break;
            static_assert(NR == 13, "one case per register set");
            switch (ri) {
                ECA_CASE(0) ECA_CASE(1) ECA_CASE(2) ECA_CASE(3) ECA_CASE(4) ECA_CASE(5) ECA_CASE(6)
                ECA_CASE(7) ECA_CASE(8) ECA_CASE(9) ECA_CASE(10) ECA_CASE(11) ECA_CASE(12)
                default: break;
            }
#undef ECA_CASE
            if (k + NR + NS / G < n) { __syncwarp(); mbar_arrive_elect(empty + ref_slot * 8 + (dep & zero)); }
            if (++ri == NR) ri = 0;
            ref_slot += G; if (ref_slot >= NS) ref_slot -= NS;
        }
    }
}

}

namespace eca_fb {
__device__ float g_part[256][eca::CH];
__global__ void sum_kernel(const __nv_bfloat16* __restrict__ x, int rows) {
    const int c = threadIdx.x; float a = 0.f;
    for (int r = blockIdx.x; r < rows; r += gridDim.x) a += __bfloat162float(x[(size_t)r * eca::CH + c]);
    g_part[blockIdx.x][c] = a;
}
__global__ void scale_kernel(const __nv_bfloat16* __restrict__ x, const __nv_bfloat16* __restrict__ w, __nv_bfloat16* __restrict__ y, int rows) {
    const int c = threadIdx.x; double t = 0.0;
    for (int i = 0; i < 256; i++) t += g_part[i][c];
    const float g = eca::bf_round(eca::bf_round((float)t) / (float)rows);
    const float z = eca::bf_round(g * __bfloat162float(w[0]));
    const __nv_bfloat16 s = __float2bfloat16_rn(1.f / (1.f + expf(-z)));
    for (int r = blockIdx.x; r < rows; r += gridDim.x) y[(size_t)r * eca::CH + c] = __hmul(x[(size_t)r * eca::CH + c], s);
}
}

typedef CUresult (*EncodeFn)(CUtensorMap*, CUtensorMapDataType, cuuint32_t, void*, const cuuint64_t*, const cuuint64_t*,
                             const cuuint32_t*, const cuuint32_t*, CUtensorMapInterleave, CUtensorMapSwizzle,
                             CUtensorMapL2promotion, CUtensorMapFloatOOBfill);

extern "C" void kernel_launch(void* const* d_in, const int* in_sizes, int n_in, void* d_out, int out_size) {
    using namespace eca;
    const __nv_bfloat16* x = (const __nv_bfloat16*)d_in[0];
    const __nv_bfloat16* w = (const __nv_bfloat16*)d_in[1];
    static int mode = -1;
    static EncodeFn enc = nullptr;
    if (mode < 0) {
        int dev = 0, sms = 0, occ = 0;
        cudaGetDevice(&dev);
        cudaDeviceGetAttribute(&sms, cudaDevAttrMultiProcessorCount, dev);
        cudaDriverEntryPointQueryResult q;
        cudaGetDriverEntryPoint("cuTensorMapEncodeTiled", (void**)&enc, cudaEnableDefault, &q);
        cudaError_t e = cudaFuncSetAttribute(eca_kernel, cudaFuncAttributeMaxDynamicSharedMemorySize, SM_TOTAL);
        if (e == cudaSuccess) e = cudaOccupancyMaxActiveBlocksPerMultiprocessor(&occ, eca_kernel, NTHREADS, SM_TOTAL);
        mode = (e == cudaSuccess && enc && sms * occ >= NCTA) ? 1 : 0;
        (void)cudaGetLastError();
    }
    CUtensorMap tm;
    bool fast = mode == 1 && in_sizes[0] == ROWS * CH && out_size == ROWS * CH;
    if (fast) {
        cuuint64_t dims[2] = {(cuuint64_t)CH, (cuuint64_t)ROWS}; cuuint64_t strides[1] = {(cuuint64_t)ROWB};
        cuuint32_t box[2] = {128, (cuuint32_t)TR}; cuuint32_t es[2] = {1, 1};
        fast = enc(&tm, CU_TENSOR_MAP_DATA_TYPE_BFLOAT16, 2, (void*)x, dims, strides, box, es, CU_TENSOR_MAP_INTERLEAVE_NONE,
                   CU_TENSOR_MAP_SWIZZLE_NONE, CU_TENSOR_MAP_L2_PROMOTION_NONE, CU_TENSOR_MAP_FLOAT_OOB_FILL_NONE) == CUDA_SUCCESS;
    }
    if (fast) {
        cudaLaunchAttribute at;
        at.id = cudaLaunchAttributeCooperative; at.val.cooperative = 1;
        cudaLaunchConfig_t cfg = {};
        cfg.gridDim = dim3(NCTA); cfg.blockDim = dim3(NTHREADS); cfg.dynamicSmemBytes = SM_TOTAL;
        cfg.attrs = &at; cfg.numAttrs = 1;
        cudaLaunchKernelEx(&cfg, eca_kernel, tm, w, (const char*)x, (char*)d_out, 0u);
    } else {
        const int rows = in_sizes[0] / CH;
        eca_fb::sum_kernel<<<256, CH>>>(x, rows);
        eca_fb::scale_kernel<<<1024, CH>>>(x, w, (__nv_bfloat16*)d_out, rows);
    }
}
```
